```python
import torch

def _softmax(x, axis=-1):
    return torch.softmax(x, dim=axis)
def _gelu(x):
    return torch.nn.functional.gelu(x, approximate="tanh")
def _silu(x):
    return torch.nn.functional.silu(x)
def _sigmoid(x):
    return torch.sigmoid(x)
def _layernorm(x, axis=-1, eps=1e-5):
    m = x.mean(dim=axis, keepdim=True)
    v = x.var(dim=axis, keepdim=True, unbiased=False)
    return (x - m) / torch.sqrt(v + eps)
def _scatter_add(tgt, idx, src, axis=0):
    return tgt.clone().index_add_(axis, idx, src)
def _segment_sum(src, seg, n):
    out = torch.zeros((n,) + src.shape[1:], dtype=src.dtype)
    return out.index_add_(0, seg, src)
def _pad(x, pw):
    flat = tuple(v for pair in reversed(pw) for v in pair)
    return torch.nn.functional.pad(x, flat)

kernel_name = 'recurrent_scan__compressed_kv_cla__dense_activation_relu__prompt'

def setup_inputs():

    _w = (lambda a: (lambda t: t.to(torch.bfloat16) if t.is_floating_point() else t)(torch.as_tensor(a)))
    def _A_setup():
        B, H, Sq, Sk, D, M = 1, 32, 2048, 2048, 128, 512
        Dc = 4 * D
        return {
            "x": _w((lambda *s: torch.randn(*s, dtype=torch.bfloat16) * 0.05)(B, Sq, M)),
            "c_kv": _w((lambda *s: torch.randn(*s, dtype=torch.bfloat16) * 0.2)(B, Sk, Dc)),
            "w_q": _w((lambda *s: torch.randn(*s, dtype=torch.bfloat16) * 3.2)(M, H, D) * (M ** -0.5)),
            "w_uk": _w((lambda *s: torch.randn(*s, dtype=torch.bfloat16) * 3.2)(Dc, H, D) * (Dc ** -0.5)),
            "w_uv": _w((lambda *s: torch.randn(*s, dtype=torch.bfloat16) * 0.2)(Dc, H, D) * (Dc ** -0.5)),
            "w_o": _w((lambda *s: torch.randn(*s, dtype=torch.bfloat16) * 0.2)(H, D, M) * ((H * D) ** -0.5)),
        }
    _A_in = _A_setup()

    def _B_setup():
        B, S, D, Dff = 1, 2048, 512, 1792
        return {
            "x": _w((lambda *s: torch.randn(*s, dtype=torch.bfloat16) * 0.05)(B, S, D)),
            "w1": _w((lambda *s: torch.randn(*s, dtype=torch.bfloat16) * 0.1)(D, Dff)),
            "w2": _w((lambda *s: torch.randn(*s, dtype=torch.bfloat16) * 0.1)(Dff, D)),
        }
    _B_in = _B_setup()

    return {
        "A_x": _A_in["x"],
        "A_c_kv": _A_in["c_kv"],
        "A_w_q": _A_in["w_q"],
        "A_w_uk": _A_in["w_uk"],
        "A_w_uv": _A_in["w_uv"],
        "A_w_o": _A_in["w_o"],
        "B_x": _B_in["x"],
        "B_w1": _B_in["w1"],
        "B_w2": _B_in["w2"],
    }

def reference(A_x, A_c_kv, A_w_q, A_w_uk, A_w_uv, A_w_o, B_x, B_w1, B_w2):
    def _A_ref(x, c_kv, w_q, w_uk, w_uv, w_o):
        B, Sq, M = x.shape[0], x.shape[1], x.shape[2]
        Sk = c_kv.shape[1]
        H, D = w_q.shape[1], w_q.shape[2]
        q = torch.einsum("bqm,mhd->bhqd", x, w_q)
        k = torch.einsum("bkc,chd->bhkd", c_kv, w_uk)
        v = torch.einsum("bkc,chd->bhkd", c_kv, w_uv)
        scores = torch.einsum("bhqd,bhkd->bhqk", q, k) * (D ** -0.5)
        off = Sk - Sq
        qi = torch.arange(Sq)[:, None]
        kj = torch.arange(Sk)[None, :]
        cmask = kj <= (qi + off)
        scores = torch.where(cmask[None, None], scores, -1e9)
        p = _softmax(scores, axis=-1)
        ctx = torch.einsum("bhqk,bhkd->bhqd", p, v)
        return torch.einsum("bhqd,hdm->bqm", ctx, w_o)

    def _B_ref(x, w1, w2):
        h = torch.einsum("bsd,df->bsf", x, w1)
        zero = torch.zeros_like(h)
        h = torch.maximum(h, zero)
        return torch.einsum("bsf,fd->bsd", h, w2)

    x = A_x
    xn = _layernorm(x, axis=-1)
    s = _A_ref(xn, A_c_kv, A_w_q, A_w_uk, A_w_uv, A_w_o)
    g = _silu(_B_ref(xn, B_w1, B_w2))
    return x + s * g
```

```cpp
#include <cuda_runtime.h>
#include <cuda_bf16.h>
#include <cuda.h>
#include <stdint.h>

typedef __nv_bfloat16 bf16;

namespace {

constexpr int SEQ = 2048;
constexpr int DM  = 512;
constexpr int NH  = 32;
constexpr int HD  = 128;
constexpr int HDT = NH * HD;
constexpr int DFF = 1792;

__device__ __align__(1024) bf16 g_xn[SEQ * DM];
__device__ __align__(1024) bf16 g_q[SEQ * HDT];
__device__ __align__(1024) bf16 g_k[SEQ * HDT];
__device__ __align__(1024) bf16 g_v[SEQ * HDT];
__device__ __align__(1024) bf16 g_h[SEQ * DFF];
__device__ __align__(1024) bf16 g_ctx[SEQ * HDT];

__device__ __forceinline__ uint32_t smem_u32(const void* p) { return (uint32_t)__cvta_generic_to_shared(p); }

__device__ __forceinline__ void mbar_init(uint32_t bar, uint32_t cnt) {
  asm volatile("mbarrier.init.shared::cta.b64 [%0], %1;" ::"r"(bar), "r"(cnt));
}
__device__ __forceinline__ void mbar_expect_tx(uint32_t bar, uint32_t bytes) {
  asm volatile("mbarrier.arrive.expect_tx.shared::cta.b64 _, [%0], %1;" ::"r"(bar), "r"(bytes) : "memory");
}
__device__ __forceinline__ void mbar_arrive(uint32_t bar) {
  asm volatile("mbarrier.arrive.shared::cta.b64 _, [%0];" ::"r"(bar) : "memory");
}
__device__ __forceinline__ void mbar_arrive_cluster(uint32_t bar, uint32_t cta) {
  asm volatile("{\n.reg .b32 ra;\nmapa.shared::cluster.u32 ra, %0, %1;\nmbarrier.arrive.shared::cluster.b64 _, [ra];\n}\n" ::"r"(bar), "r"(cta) : "memory");
}
__device__ __forceinline__ bool mbar_try_wait(uint32_t bar, uint32_t parity) {
  uint32_t ok;
  asm volatile("{\n.reg .pred p;\nmbarrier.try_wait.parity.shared::cta.b64 p, [%1], %2;\nselp.u32 %0, 1, 0, p;\n}\n" : "=r"(ok) : "r"(bar), "r"(parity) : "memory");
  return ok != 0;
}
__device__ __forceinline__ void mbar_wait(uint32_t bar, uint32_t parity) {
  while (!mbar_try_wait(bar, parity)) {}
}
__device__ __forceinline__ void fence_barrier_init() { asm volatile("fence.mbarrier_init.release.cluster;" ::: "memory"); }
__device__ __forceinline__ void fence_proxy_async() { asm volatile("fence.proxy.async;" ::: "memory"); }
__device__ __forceinline__ void fence_proxy_async_smem() { asm volatile("fence.proxy.async.shared::cta;" ::: "memory"); }

__device__ __forceinline__ void tma_load_2d(uint32_t dst, const CUtensorMap* tm, uint32_t bar, int c0, int c1) {
  asm volatile("cp.async.bulk.tensor.2d.shared::cluster.global.mbarrier::complete_tx::bytes [%0], [%1, {%3, %4}], [%2];"
               ::"r"(dst), "l"(tm), "r"(bar), "r"(c0), "r"(c1) : "memory");
}
__device__ __forceinline__ void tma_load_2d_mc(uint32_t dst, const CUtensorMap* tm, uint32_t bar, int c0, int c1, uint16_t mask) {
  asm volatile("cp.async.bulk.tensor.2d.shared::cluster.global.mbarrier::complete_tx::bytes.multicast::cluster [%0], [%1, {%3, %4}], [%2], %5;"
               ::"r"(dst), "l"(tm), "r"(bar), "r"(c0), "r"(c1), "h"(mask) : "memory");
}
__device__ __forceinline__ void tma_store_2d(const CUtensorMap* tm, uint32_t src, int c0, int c1) {
  asm volatile("cp.async.bulk.tensor.2d.global.shared::cta.bulk_group [%0, {%2, %3}], [%1];"
               ::"l"(tm), "r"(src), "r"(c0), "r"(c1) : "memory");
}
__device__ __forceinline__ void tma_store_commit() { asm volatile("cp.async.bulk.commit_group;" ::: "memory"); }
template <int N> __device__ __forceinline__ void tma_store_wait_read() { asm volatile("cp.async.bulk.wait_group.read %0;" ::"n"(N) : "memory"); }
template <int N> __device__ __forceinline__ void tma_store_wait() { asm volatile("cp.async.bulk.wait_group %0;" ::"n"(N) : "memory"); }
__device__ __forceinline__ void prefetch_tmap(const CUtensorMap* tm) { asm volatile("prefetch.tensormap [%0];" ::"l"(tm) : "memory"); }

__device__ __forceinline__ void named_bar_sync(int id, int nthreads) { asm volatile("bar.sync %0, %1;" ::"r"(id), "r"(nthreads) : "memory"); }
__device__ __forceinline__ void named_bar_arrive(int id, int nthreads) { asm volatile("bar.arrive %0, %1;" ::"r"(id), "r"(nthreads) : "memory"); }

__device__ __forceinline__ uint32_t cluster_ctarank() { uint32_t r; asm volatile("mov.u32 %0, %%cluster_ctarank;" : "=r"(r)); return r; }
__device__ __forceinline__ void cluster_sync_all() { asm volatile("barrier.cluster.arrive.release.aligned;\nbarrier.cluster.wait.acquire.aligned;" ::: "memory"); }

template <int R> __device__ __forceinline__ void reg_alloc() { asm volatile("setmaxnreg.inc.sync.aligned.u32 %0;" ::"n"(R)); }
template <int R> __device__ __forceinline__ void reg_dealloc() { asm volatile("setmaxnreg.dec.sync.aligned.u32 %0;" ::"n"(R)); }

__device__ __forceinline__ void wgmma_fence() { asm volatile("wgmma.fence.sync.aligned;" ::: "memory"); }
__device__ __forceinline__ void wgmma_commit() { asm volatile("wgmma.commit_group.sync.aligned;" ::: "memory"); }
template <int N> __device__ __forceinline__ void wgmma_wait() { asm volatile("wgmma.wait_group.sync.aligned %0;" ::"n"(N) : "memory"); }

__device__ __forceinline__ uint64_t make_desc(uint32_t saddr, uint32_t lbo, uint32_t sbo) {
  uint64_t d = 0;
  d |= (uint64_t)((saddr & 0x3FFFF) >> 4);
  d |= (uint64_t)((lbo & 0x3FFFF) >> 4) << 16;
  d |= (uint64_t)((sbo & 0x3FFFF) >> 4) << 32;
  d |= (uint64_t)1 << 62;
  return d;
}

__device__ __forceinline__ uint32_t pack_bf16(float lo, float hi) {
  uint32_t r;
  asm("cvt.rn.bf16x2.f32 %0, %1, %2;" : "=r"(r) : "f"(hi), "f"(lo));
  return r;
}
__device__ __forceinline__ float ex2(float x) { float y; asm("ex2.approx.ftz.f32 %0, %1;" : "=f"(y) : "f"(x)); return y; }

template<int TB> __device__ __forceinline__ void wgmma_m64n128k16_ss(float (&d)[64], uint64_t da, uint64_t db, int scale_d) {
  asm volatile("{\n.reg .pred p;\nsetp.ne.b32 p, %66, 0;\nwgmma.mma_async.sync.aligned.m64n128k16.f32.bf16.bf16 {%0, %1, %2, %3, %4, %5, %6, %7, %8, %9, %10, %11, %12, %13, %14, %15, %16, %17, %18, %19, %20, %21, %22, %23, %24, %25, %26, %27, %28, %29, %30, %31, %32, %33, %34, %35, %36, %37, %38, %39, %40, %41, %42, %43, %44, %45, %46, %47, %48, %49, %50, %51, %52, %53, %54, %55, %56, %57, %58, %59, %60, %61, %62, %63}, %64, %65, p, 1, 1, 0, %67;\n}\n"
    : "+f"(d[0]), "+f"(d[1]), "+f"(d[2]), "+f"(d[3]), "+f"(d[4]), "+f"(d[5]), "+f"(d[6]), "+f"(d[7]), "+f"(d[8]), "+f"(d[9]), "+f"(d[10]), "+f"(d[11]), "+f"(d[12]), "+f"(d[13]), "+f"(d[14]), "+f"(d[15]), "+f"(d[16]), "+f"(d[17]), "+f"(d[18]), "+f"(d[19]), "+f"(d[20]), "+f"(d[21]), "+f"(d[22]), "+f"(d[23]), "+f"(d[24]), "+f"(d[25]), "+f"(d[26]), "+f"(d[27]), "+f"(d[28]), "+f"(d[29]), "+f"(d[30]), "+f"(d[31]), "+f"(d[32]), "+f"(d[33]), "+f"(d[34]), "+f"(d[35]), "+f"(d[36]), "+f"(d[37]), "+f"(d[38]), "+f"(d[39]), "+f"(d[40]), "+f"(d[41]), "+f"(d[42]), "+f"(d[43]), "+f"(d[44]), "+f"(d[45]), "+f"(d[46]), "+f"(d[47]), "+f"(d[48]), "+f"(d[49]), "+f"(d[50]), "+f"(d[51]), "+f"(d[52]), "+f"(d[53]), "+f"(d[54]), "+f"(d[55]), "+f"(d[56]), "+f"(d[57]), "+f"(d[58]), "+f"(d[59]), "+f"(d[60]), "+f"(d[61]), "+f"(d[62]), "+f"(d[63])
    : "l"(da), "l"(db), "r"(scale_d), "n"(TB));
}

template<int TB> __device__ __forceinline__ void wgmma_m64n128k16_rs(float (&d)[64], uint32_t a0, uint32_t a1, uint32_t a2, uint32_t a3, uint64_t db, int scale_d) {
  asm volatile("{\n.reg .pred p;\nsetp.ne.b32 p, %69, 0;\nwgmma.mma_async.sync.aligned.m64n128k16.f32.bf16.bf16 {%0, %1, %2, %3, %4, %5, %6, %7, %8, %9, %10, %11, %12, %13, %14, %15, %16, %17, %18, %19, %20, %21, %22, %23, %24, %25, %26, %27, %28, %29, %30, %31, %32, %33, %34, %35, %36, %37, %38, %39, %40, %41, %42, %43, %44, %45, %46, %47, %48, %49, %50, %51, %52, %53, %54, %55, %56, %57, %58, %59, %60, %61, %62, %63}, {%64, %65, %66, %67}, %68, p, 1, 1, %70;\n}\n"
    : "+f"(d[0]), "+f"(d[1]), "+f"(d[2]), "+f"(d[3]), "+f"(d[4]), "+f"(d[5]), "+f"(d[6]), "+f"(d[7]), "+f"(d[8]), "+f"(d[9]), "+f"(d[10]), "+f"(d[11]), "+f"(d[12]), "+f"(d[13]), "+f"(d[14]), "+f"(d[15]), "+f"(d[16]), "+f"(d[17]), "+f"(d[18]), "+f"(d[19]), "+f"(d[20]), "+f"(d[21]), "+f"(d[22]), "+f"(d[23]), "+f"(d[24]), "+f"(d[25]), "+f"(d[26]), "+f"(d[27]), "+f"(d[28]), "+f"(d[29]), "+f"(d[30]), "+f"(d[31]), "+f"(d[32]), "+f"(d[33]), "+f"(d[34]), "+f"(d[35]), "+f"(d[36]), "+f"(d[37]), "+f"(d[38]), "+f"(d[39]), "+f"(d[40]), "+f"(d[41]), "+f"(d[42]), "+f"(d[43]), "+f"(d[44]), "+f"(d[45]), "+f"(d[46]), "+f"(d[47]), "+f"(d[48]), "+f"(d[49]), "+f"(d[50]), "+f"(d[51]), "+f"(d[52]), "+f"(d[53]), "+f"(d[54]), "+f"(d[55]), "+f"(d[56]), "+f"(d[57]), "+f"(d[58]), "+f"(d[59]), "+f"(d[60]), "+f"(d[61]), "+f"(d[62]), "+f"(d[63])
    : "r"(a0), "r"(a1), "r"(a2), "r"(a3), "l"(db), "r"(scale_d), "n"(TB));
}

template<int TB> __device__ __forceinline__ void wgmma_m64n256k16_ss(float (&d)[128], uint64_t da, uint64_t db, int scale_d) {
  asm volatile("{\n.reg .pred p;\nsetp.ne.b32 p, %130, 0;\nwgmma.mma_async.sync.aligned.m64n256k16.f32.bf16.bf16 {%0, %1, %2, %3, %4, %5, %6, %7, %8, %9, %10, %11, %12, %13, %14, %15, %16, %17, %18, %19, %20, %21, %22, %23, %24, %25, %26, %27, %28, %29, %30, %31, %32, %33, %34, %35, %36, %37, %38, %39, %40, %41, %42, %43, %44, %45, %46, %47, %48, %49, %50, %51, %52, %53, %54, %55, %56, %57, %58, %59, %60, %61, %62, %63, %64, %65, %66, %67, %68, %69, %70, %71, %72, %73, %74, %75, %76, %77, %78, %79, %80, %81, %82, %83, %84, %85, %86, %87, %88, %89, %90, %91, %92, %93, %94, %95, %96, %97, %98, %99, %100, %101, %102, %103, %104, %105, %106, %107, %108, %109, %110, %111, %112, %113, %114, %115, %116, %117, %118, %119, %120, %121, %122, %123, %124, %125, %126, %127}, %128, %129, p, 1, 1, 0, %131;\n}\n"
    : "+f"(d[0]), "+f"(d[1]), "+f"(d[2]), "+f"(d[3]), "+f"(d[4]), "+f"(d[5]), "+f"(d[6]), "+f"(d[7]), "+f"(d[8]), "+f"(d[9]), "+f"(d[10]), "+f"(d[11]), "+f"(d[12]), "+f"(d[13]), "+f"(d[14]), "+f"(d[15]), "+f"(d[16]), "+f"(d[17]), "+f"(d[18]), "+f"(d[19]), "+f"(d[20]), "+f"(d[21]), "+f"(d[22]), "+f"(d[23]), "+f"(d[24]), "+f"(d[25]), "+f"(d[26]), "+f"(d[27]), "+f"(d[28]), "+f"(d[29]), "+f"(d[30]), "+f"(d[31]), "+f"(d[32]), "+f"(d[33]), "+f"(d[34]), "+f"(d[35]), "+f"(d[36]), "+f"(d[37]), "+f"(d[38]), "+f"(d[39]), "+f"(d[40]), "+f"(d[41]), "+f"(d[42]), "+f"(d[43]), "+f"(d[44]), "+f"(d[45]), "+f"(d[46]), "+f"(d[47]), "+f"(d[48]), "+f"(d[49]), "+f"(d[50]), "+f"(d[51]), "+f"(d[52]), "+f"(d[53]), "+f"(d[54]), "+f"(d[55]), "+f"(d[56]), "+f"(d[57]), "+f"(d[58]), "+f"(d[59]), "+f"(d[60]), "+f"(d[61]), "+f"(d[62]), "+f"(d[63]), "+f"(d[64]), "+f"(d[65]), "+f"(d[66]), "+f"(d[67]), "+f"(d[68]), "+f"(d[69]), "+f"(d[70]), "+f"(d[71]), "+f"(d[72]), "+f"(d[73]), "+f"(d[74]), "+f"(d[75]), "+f"(d[76]), "+f"(d[77]), "+f"(d[78]), "+f"(d[79]), "+f"(d[80]), "+f"(d[81]), "+f"(d[82]), "+f"(d[83]), "+f"(d[84]), "+f"(d[85]), "+f"(d[86]), "+f"(d[87]), "+f"(d[88]), "+f"(d[89]), "+f"(d[90]), "+f"(d[91]), "+f"(d[92]), "+f"(d[93]), "+f"(d[94]), "+f"(d[95]), "+f"(d[96]), "+f"(d[97]), "+f"(d[98]), "+f"(d[99]), "+f"(d[100]), "+f"(d[101]), "+f"(d[102]), "+f"(d[103]), "+f"(d[104]), "+f"(d[105]), "+f"(d[106]), "+f"(d[107]), "+f"(d[108]), "+f"(d[109]), "+f"(d[110]), "+f"(d[111]), "+f"(d[112]), "+f"(d[113]), "+f"(d[114]), "+f"(d[115]), "+f"(d[116]), "+f"(d[117]), "+f"(d[118]), "+f"(d[119]), "+f"(d[120]), "+f"(d[121]), "+f"(d[122]), "+f"(d[123]), "+f"(d[124]), "+f"(d[125]), "+f"(d[126]), "+f"(d[127])
    : "l"(da), "l"(db), "r"(scale_d), "n"(TB));
}

template<int TB> __device__ __forceinline__ void wgmma_m64n64k16_ss(float (&d)[32], uint64_t da, uint64_t db, int scale_d) {
  asm volatile("{\n.reg .pred p;\nsetp.ne.b32 p, %34, 0;\nwgmma.mma_async.sync.aligned.m64n64k16.f32.bf16.bf16 {%0, %1, %2, %3, %4, %5, %6, %7, %8, %9, %10, %11, %12, %13, %14, %15, %16, %17, %18, %19, %20, %21, %22, %23, %24, %25, %26, %27, %28, %29, %30, %31}, %32, %33, p, 1, 1, 0, %35;\n}\n"
    : "+f"(d[0]), "+f"(d[1]), "+f"(d[2]), "+f"(d[3]), "+f"(d[4]), "+f"(d[5]), "+f"(d[6]), "+f"(d[7]), "+f"(d[8]), "+f"(d[9]), "+f"(d[10]), "+f"(d[11]), "+f"(d[12]), "+f"(d[13]), "+f"(d[14]), "+f"(d[15]), "+f"(d[16]), "+f"(d[17]), "+f"(d[18]), "+f"(d[19]), "+f"(d[20]), "+f"(d[21]), "+f"(d[22]), "+f"(d[23]), "+f"(d[24]), "+f"(d[25]), "+f"(d[26]), "+f"(d[27]), "+f"(d[28]), "+f"(d[29]), "+f"(d[30]), "+f"(d[31])
    : "l"(da), "l"(db), "r"(scale_d), "n"(TB));
}

template<int TB> __device__ __forceinline__ void wgmma_m64n64k16_rs(float (&d)[32], uint32_t a0, uint32_t a1, uint32_t a2, uint32_t a3, uint64_t db, int scale_d) {
  asm volatile("{\n.reg .pred p;\nsetp.ne.b32 p, %37, 0;\nwgmma.mma_async.sync.aligned.m64n64k16.f32.bf16.bf16 {%0, %1, %2, %3, %4, %5, %6, %7, %8, %9, %10, %11, %12, %13, %14, %15, %16, %17, %18, %19, %20, %21, %22, %23, %24, %25, %26, %27, %28, %29, %30, %31}, {%32, %33, %34, %35}, %36, p, 1, 1, %38;\n}\n"
    : "+f"(d[0]), "+f"(d[1]), "+f"(d[2]), "+f"(d[3]), "+f"(d[4]), "+f"(d[5]), "+f"(d[6]), "+f"(d[7]), "+f"(d[8]), "+f"(d[9]), "+f"(d[10]), "+f"(d[11]), "+f"(d[12]), "+f"(d[13]), "+f"(d[14]), "+f"(d[15]), "+f"(d[16]), "+f"(d[17]), "+f"(d[18]), "+f"(d[19]), "+f"(d[20]), "+f"(d[21]), "+f"(d[22]), "+f"(d[23]), "+f"(d[24]), "+f"(d[25]), "+f"(d[26]), "+f"(d[27]), "+f"(d[28]), "+f"(d[29]), "+f"(d[30]), "+f"(d[31])
    : "r"(a0), "r"(a1), "r"(a2), "r"(a3), "l"(db), "r"(scale_d), "n"(TB));
}

__device__ __forceinline__ void reg_fence(float (&d)[32]) {
  asm volatile("" : "+f"(d[0]), "+f"(d[1]), "+f"(d[2]), "+f"(d[3]), "+f"(d[4]), "+f"(d[5]), "+f"(d[6]), "+f"(d[7]), "+f"(d[8]), "+f"(d[9]), "+f"(d[10]), "+f"(d[11]), "+f"(d[12]), "+f"(d[13]), "+f"(d[14]), "+f"(d[15]), "+f"(d[16]), "+f"(d[17]), "+f"(d[18]), "+f"(d[19]), "+f"(d[20]), "+f"(d[21]), "+f"(d[22]), "+f"(d[23]), "+f"(d[24]), "+f"(d[25]), "+f"(d[26]), "+f"(d[27]), "+f"(d[28]), "+f"(d[29]), "+f"(d[30]), "+f"(d[31]) :: "memory");
}

__device__ __forceinline__ void reg_fence(float (&d)[64]) {
  asm volatile("" : "+f"(d[0]), "+f"(d[1]), "+f"(d[2]), "+f"(d[3]), "+f"(d[4]), "+f"(d[5]), "+f"(d[6]), "+f"(d[7]), "+f"(d[8]), "+f"(d[9]), "+f"(d[10]), "+f"(d[11]), "+f"(d[12]), "+f"(d[13]), "+f"(d[14]), "+f"(d[15]), "+f"(d[16]), "+f"(d[17]), "+f"(d[18]), "+f"(d[19]), "+f"(d[20]), "+f"(d[21]), "+f"(d[22]), "+f"(d[23]), "+f"(d[24]), "+f"(d[25]), "+f"(d[26]), "+f"(d[27]), "+f"(d[28]), "+f"(d[29]), "+f"(d[30]), "+f"(d[31]), "+f"(d[32]), "+f"(d[33]), "+f"(d[34]), "+f"(d[35]), "+f"(d[36]), "+f"(d[37]), "+f"(d[38]), "+f"(d[39]), "+f"(d[40]), "+f"(d[41]), "+f"(d[42]), "+f"(d[43]), "+f"(d[44]), "+f"(d[45]), "+f"(d[46]), "+f"(d[47]), "+f"(d[48]), "+f"(d[49]), "+f"(d[50]), "+f"(d[51]), "+f"(d[52]), "+f"(d[53]), "+f"(d[54]), "+f"(d[55]), "+f"(d[56]), "+f"(d[57]), "+f"(d[58]), "+f"(d[59]), "+f"(d[60]), "+f"(d[61]), "+f"(d[62]), "+f"(d[63]) :: "memory");
}

__device__ __forceinline__ void reg_fence(float (&d)[128]) {
  asm volatile("" : "+f"(d[0]), "+f"(d[1]), "+f"(d[2]), "+f"(d[3]), "+f"(d[4]), "+f"(d[5]), "+f"(d[6]), "+f"(d[7]), "+f"(d[8]), "+f"(d[9]), "+f"(d[10]), "+f"(d[11]), "+f"(d[12]), "+f"(d[13]), "+f"(d[14]), "+f"(d[15]), "+f"(d[16]), "+f"(d[17]), "+f"(d[18]), "+f"(d[19]), "+f"(d[20]), "+f"(d[21]), "+f"(d[22]), "+f"(d[23]), "+f"(d[24]), "+f"(d[25]), "+f"(d[26]), "+f"(d[27]), "+f"(d[28]), "+f"(d[29]), "+f"(d[30]), "+f"(d[31]), "+f"(d[32]), "+f"(d[33]), "+f"(d[34]), "+f"(d[35]), "+f"(d[36]), "+f"(d[37]), "+f"(d[38]), "+f"(d[39]), "+f"(d[40]), "+f"(d[41]), "+f"(d[42]), "+f"(d[43]), "+f"(d[44]), "+f"(d[45]), "+f"(d[46]), "+f"(d[47]), "+f"(d[48]), "+f"(d[49]), "+f"(d[50]), "+f"(d[51]), "+f"(d[52]), "+f"(d[53]), "+f"(d[54]), "+f"(d[55]), "+f"(d[56]), "+f"(d[57]), "+f"(d[58]), "+f"(d[59]), "+f"(d[60]), "+f"(d[61]), "+f"(d[62]), "+f"(d[63]), "+f"(d[64]), "+f"(d[65]), "+f"(d[66]), "+f"(d[67]), "+f"(d[68]), "+f"(d[69]), "+f"(d[70]), "+f"(d[71]), "+f"(d[72]), "+f"(d[73]), "+f"(d[74]), "+f"(d[75]), "+f"(d[76]), "+f"(d[77]), "+f"(d[78]), "+f"(d[79]), "+f"(d[80]), "+f"(d[81]), "+f"(d[82]), "+f"(d[83]), "+f"(d[84]), "+f"(d[85]), "+f"(d[86]), "+f"(d[87]), "+f"(d[88]), "+f"(d[89]), "+f"(d[90]), "+f"(d[91]), "+f"(d[92]), "+f"(d[93]), "+f"(d[94]), "+f"(d[95]), "+f"(d[96]), "+f"(d[97]), "+f"(d[98]), "+f"(d[99]), "+f"(d[100]), "+f"(d[101]), "+f"(d[102]), "+f"(d[103]), "+f"(d[104]), "+f"(d[105]), "+f"(d[106]), "+f"(d[107]), "+f"(d[108]), "+f"(d[109]), "+f"(d[110]), "+f"(d[111]), "+f"(d[112]), "+f"(d[113]), "+f"(d[114]), "+f"(d[115]), "+f"(d[116]), "+f"(d[117]), "+f"(d[118]), "+f"(d[119]), "+f"(d[120]), "+f"(d[121]), "+f"(d[122]), "+f"(d[123]), "+f"(d[124]), "+f"(d[125]), "+f"(d[126]), "+f"(d[127]) :: "memory");
}

#define ATT_PINGPONG 1
#define TR(ev) do {} while (0)
#define TI(ev) do {} while (0)
constexpr int ATT_K_ST = 3, ATT_V_ST = 2;
constexpr int ATT_TILE_BYTES = 128 * 128 * 2;
struct AttnSmem {
  uint8_t q[ATT_TILE_BYTES];
  uint8_t k[ATT_K_ST][ATT_TILE_BYTES];
  uint8_t v[ATT_V_ST][ATT_TILE_BYTES];
  uint8_t ostage[ATT_TILE_BYTES];
  uint64_t q_full, q_empty;
  uint64_t k_full[ATT_K_ST], k_empty[ATT_K_ST], v_full[ATT_V_ST], v_empty[ATT_V_ST];
};
constexpr int ATT_SMEM_BYTES = sizeof(AttnSmem) + 1024;
constexpr int ATT_ITEMS_PER_CTA = 4;

__device__ __forceinline__ void attn_item(int cta, int it, int& head, int& qt) {
  head = 8 * it + (cta >> 4);
  int r = cta & 15;
  qt = (it & 1) ? (15 - r) : r;
}

__global__ void __launch_bounds__(384, 1)
attn_kernel(const __grid_constant__ CUtensorMap tmQ, const __grid_constant__ CUtensorMap tmK,
            const __grid_constant__ CUtensorMap tmV, const __grid_constant__ CUtensorMap tmO) {
  extern __shared__ uint8_t smem_raw[];
  AttnSmem& sm = *reinterpret_cast<AttnSmem*>((reinterpret_cast<uintptr_t>(smem_raw) + 1023) & ~uintptr_t(1023));
  const int wg = threadIdx.x >> 7;
  const int cta = blockIdx.x;

  if (threadIdx.x == 0) {
    mbar_init(smem_u32(&sm.q_full), 1);
    mbar_init(smem_u32(&sm.q_empty), 8);
    for (int s = 0; s < ATT_K_ST; s++) {
      mbar_init(smem_u32(&sm.k_full[s]), 1);
      mbar_init(smem_u32(&sm.k_empty[s]), 8);
    }
    for (int s = 0; s < ATT_V_ST; s++) {
      mbar_init(smem_u32(&sm.v_full[s]), 1);
      mbar_init(smem_u32(&sm.v_empty[s]), 8);
    }
    fence_barrier_init();
  }
  __syncthreads();

  if (wg == 0) {
    reg_dealloc<40>();
    if (threadIdx.x == 0) {
      int kst = 0, vst = 0; uint32_t kph = 0, vph = 0;
      for (int it = 0; it < ATT_ITEMS_PER_CTA; it++) {
        int head, qt; attn_item(cta, it, head, qt);
        mbar_wait(smem_u32(&sm.q_empty), (it & 1) ^ 1);
        mbar_expect_tx(smem_u32(&sm.q_full), ATT_TILE_BYTES);
        tma_load_2d(smem_u32(sm.q), &tmQ, smem_u32(&sm.q_full), head * HD, qt * 128);
        tma_load_2d(smem_u32(sm.q) + 16384, &tmQ, smem_u32(&sm.q_full), head * HD + 64, qt * 128);
        for (int n = qt; n >= 0; --n) {
          mbar_wait(smem_u32(&sm.k_empty[kst]), kph ^ 1);
          mbar_expect_tx(smem_u32(&sm.k_full[kst]), ATT_TILE_BYTES);
          tma_load_2d(smem_u32(sm.k[kst]), &tmK, smem_u32(&sm.k_full[kst]), head * HD, n * 128);
          tma_load_2d(smem_u32(sm.k[kst]) + 16384, &tmK, smem_u32(&sm.k_full[kst]), head * HD + 64, n * 128);
          if (++kst == ATT_K_ST) { kst = 0; kph ^= 1; }
          mbar_wait(smem_u32(&sm.v_empty[vst]), vph ^ 1);
          mbar_expect_tx(smem_u32(&sm.v_full[vst]), ATT_TILE_BYTES);
          tma_load_2d(smem_u32(sm.v[vst]), &tmV, smem_u32(&sm.v_full[vst]), head * HD, n * 128);
          tma_load_2d(smem_u32(sm.v[vst]) + 16384, &tmV, smem_u32(&sm.v_full[vst]), head * HD + 64, n * 128);
          if (++vst == ATT_V_ST) { vst = 0; vph ^= 1; }
        }
      }
    }
  } else {
    reg_alloc<232>();
    const int cw = __shfl_sync(0xffffffffu, wg - 1, 0);
    const int tid = threadIdx.x & 127;
    const int warp = tid >> 5, lane = tid & 31;
    const float sl2 = 0.08838834764831845f * 1.4426950408889634f;
    int kst = 0, vst = 0; uint32_t kph = 0, vph = 0;
    const uint64_t q_desc = make_desc(smem_u32(sm.q) + cw * 8192, 16, 1024);
    const uint64_t k_desc = make_desc(smem_u32(sm.k[0]), 16, 1024);
    const uint64_t v_desc = make_desc(smem_u32(sm.v[0]), 16384, 1024);
    float o[64], s[64];
    uint32_t p[32];
    if (cw == 1) named_bar_arrive(1, 256);
    auto issue_qk = [&]() {
      mbar_wait(smem_u32(&sm.k_full[kst]), kph);
      const uint64_t kd = k_desc + (uint32_t)(kst * (ATT_TILE_BYTES >> 4));
      wgmma_fence();
#pragma unroll
      for (int ks = 0; ks < 8; ks++) {
        const uint32_t off = ((ks >> 2) * 16384 + (ks & 3) * 32) >> 4;
        wgmma_m64n128k16_ss<0>(s, q_desc + off, kd + off, ks > 0);
      }
      wgmma_commit();
    };
    auto issue_pv = [&]() {
      mbar_wait(smem_u32(&sm.v_full[vst]), vph);
      const uint64_t vd = v_desc + (uint32_t)(vst * (ATT_TILE_BYTES >> 4));
      wgmma_fence();
#pragma unroll
      for (int ks = 0; ks < 8; ks++) {
        wgmma_m64n128k16_rs<1>(o, p[4 * ks], p[4 * ks + 1], p[4 * ks + 2], p[4 * ks + 3], vd + (ks * 2048 >> 4), 1);
      }
      wgmma_commit();
    };
    auto release_k = [&]() {
      if (lane == 0) mbar_arrive(smem_u32(&sm.k_empty[kst]));
      if (++kst == ATT_K_ST) { kst = 0; kph ^= 1; }
    };
    auto release_v = [&]() {
      if (lane == 0) mbar_arrive(smem_u32(&sm.v_empty[vst]));
      if (++vst == ATT_V_ST) { vst = 0; vph ^= 1; }
    };
    auto sched_sync = [&]() {
      named_bar_sync(1 + cw, 256);
    };
    auto sched_arrive = [&]() {
      named_bar_arrive(1 + (cw ^ 1), 256);
    };

    for (int it = 0; it < ATT_ITEMS_PER_CTA; it++) {
      int head, qt; attn_item(cta, it, head, qt);
      float m0, m1, l0, l1, a0 = 1.f, a1 = 1.f;
#pragma unroll
      for (int i = 0; i < 64; i++) o[i] = 0.f;
      TI(0);
      mbar_wait(smem_u32(&sm.q_full), it & 1);
      TI(1);
      sched_sync();
      issue_qk();
      sched_arrive();
      wgmma_wait<0>();
      reg_fence(s);
      TI(2);
      release_k();
      if (qt == 0 && lane == 0) mbar_arrive(smem_u32(&sm.q_empty));
      {
        const int r0 = cw * 64 + warp * 16 + (lane >> 2);
#pragma unroll
        for (int j = 0; j < 16; j++) {
          int c = 8 * j + 2 * (lane & 3);
          if (c > r0) s[4 * j] = -INFINITY;
          if (c + 1 > r0) s[4 * j + 1] = -INFINITY;
          if (c > r0 + 8) s[4 * j + 2] = -INFINITY;
          if (c + 1 > r0 + 8) s[4 * j + 3] = -INFINITY;
        }
        float mx0 = fmaxf(s[0], s[1]), mx1 = fmaxf(s[2], s[3]);
#pragma unroll
        for (int j = 1; j < 16; j++) {
          mx0 = fmaxf(mx0, fmaxf(s[4 * j], s[4 * j + 1]));
          mx1 = fmaxf(mx1, fmaxf(s[4 * j + 2], s[4 * j + 3]));
        }
        mx0 = fmaxf(mx0, __shfl_xor_sync(0xffffffffu, mx0, 1));
        mx1 = fmaxf(mx1, __shfl_xor_sync(0xffffffffu, mx1, 1));
        mx0 = fmaxf(mx0, __shfl_xor_sync(0xffffffffu, mx0, 2));
        mx1 = fmaxf(mx1, __shfl_xor_sync(0xffffffffu, mx1, 2));
        m0 = mx0; m1 = mx1;
        const float ms0 = m0 * sl2, ms1 = m1 * sl2;
        l0 = 0.f; l1 = 0.f;
#pragma unroll
        for (int j = 0; j < 16; j++) {
          float p0 = ex2(fmaf(s[4 * j], sl2, -ms0));
          float p1 = ex2(fmaf(s[4 * j + 1], sl2, -ms0));
          float p2 = ex2(fmaf(s[4 * j + 2], sl2, -ms1));
          float p3 = ex2(fmaf(s[4 * j + 3], sl2, -ms1));
          l0 += p0 + p1; l1 += p2 + p3;
          p[2 * j] = pack_bf16(p0, p1);
          p[2 * j + 1] = pack_bf16(p2, p3);
        }
      }
      TI(3);
      for (int n = qt - 1; n >= 0; --n) {
        if (n != qt - 1) {
          TR(6);
          wgmma_wait<0>();
          reg_fence(o);
          TR(7);
          release_v();
#pragma unroll
          for (int j = 0; j < 16; j++) {
            p[2 * j] = pack_bf16(s[4 * j], s[4 * j + 1]);
            p[2 * j + 1] = pack_bf16(s[4 * j + 2], s[4 * j + 3]);
          }
        }
        TR(0);
        sched_sync();
        TR(1);
        issue_qk();
        TR(2);
#pragma unroll
        for (int j = 0; j < 16; j++) {
          o[4 * j] *= a0; o[4 * j + 1] *= a0; o[4 * j + 2] *= a1; o[4 * j + 3] *= a1;
        }
        issue_pv();
        TR(3);
        sched_arrive();
        wgmma_wait<1>();
        reg_fence(s);
        TR(4);
        release_k();
        if (n == 0 && lane == 0) mbar_arrive(smem_u32(&sm.q_empty));
        float mx0 = fmaxf(s[0], s[1]), mx1 = fmaxf(s[2], s[3]);
#pragma unroll
        for (int j = 1; j < 16; j++) {
          mx0 = fmaxf(mx0, fmaxf(s[4 * j], s[4 * j + 1]));
          mx1 = fmaxf(mx1, fmaxf(s[4 * j + 2], s[4 * j + 3]));
        }
        mx0 = fmaxf(mx0, __shfl_xor_sync(0xffffffffu, mx0, 1));
        mx1 = fmaxf(mx1, __shfl_xor_sync(0xffffffffu, mx1, 1));
        mx0 = fmaxf(mx0, __shfl_xor_sync(0xffffffffu, mx0, 2));
        mx1 = fmaxf(mx1, __shfl_xor_sync(0xffffffffu, mx1, 2));
        const float mn0 = fmaxf(m0, mx0), mn1 = fmaxf(m1, mx1);
        a0 = ex2((m0 - mn0) * sl2); a1 = ex2((m1 - mn1) * sl2);
        m0 = mn0; m1 = mn1;
        const float ms0 = mn0 * sl2, ms1 = mn1 * sl2;
        float rs0 = 0.f, rs1 = 0.f;
#pragma unroll
        for (int j = 0; j < 16; j++) {
          s[4 * j] = ex2(fmaf(s[4 * j], sl2, -ms0));
          s[4 * j + 1] = ex2(fmaf(s[4 * j + 1], sl2, -ms0));
          s[4 * j + 2] = ex2(fmaf(s[4 * j + 2], sl2, -ms1));
          s[4 * j + 3] = ex2(fmaf(s[4 * j + 3], sl2, -ms1));
          rs0 += s[4 * j] + s[4 * j + 1]; rs1 += s[4 * j + 2] + s[4 * j + 3];
        }
        l0 = l0 * a0 + rs0; l1 = l1 * a1 + rs1;
        reg_fence(s);
        TR(5);
      }
      if (qt > 0) {
        wgmma_wait<0>();
        reg_fence(o);
        release_v();
#pragma unroll
        for (int j = 0; j < 16; j++) {
          p[2 * j] = pack_bf16(s[4 * j], s[4 * j + 1]);
          p[2 * j + 1] = pack_bf16(s[4 * j + 2], s[4 * j + 3]);
        }
      }
      TI(4);
#pragma unroll
      for (int j = 0; j < 16; j++) {
        o[4 * j] *= a0; o[4 * j + 1] *= a0; o[4 * j + 2] *= a1; o[4 * j + 3] *= a1;
      }
      sched_sync();
      issue_pv();
      sched_arrive();
      l0 += __shfl_xor_sync(0xffffffffu, l0, 1); l0 += __shfl_xor_sync(0xffffffffu, l0, 2);
      l1 += __shfl_xor_sync(0xffffffffu, l1, 1); l1 += __shfl_xor_sync(0xffffffffu, l1, 2);
      const float inv0 = 1.f / l0, inv1 = 1.f / l1;
      wgmma_wait<0>();
      reg_fence(o);
      release_v();
      TI(5);
      if (tid == 0) tma_store_wait_read<0>();
      named_bar_sync(3 + cw, 128);
      {
        const int mi = lane >> 3;
        const int row = warp * 16 + (lane & 7) + (mi & 1) * 8;
        const uint32_t base = smem_u32(sm.ostage) + cw * 16384 + row * 128;
#pragma unroll
        for (int jj = 0; jj < 8; jj++) {
          uint32_t r0 = pack_bf16(o[8 * jj] * inv0, o[8 * jj + 1] * inv0);
          uint32_t r1 = pack_bf16(o[8 * jj + 2] * inv1, o[8 * jj + 3] * inv1);
          uint32_t r2 = pack_bf16(o[8 * jj + 4] * inv0, o[8 * jj + 5] * inv0);
          uint32_t r3 = pack_bf16(o[8 * jj + 6] * inv1, o[8 * jj + 7] * inv1);
          const int c = 2 * jj + (mi >> 1);
          const uint32_t addr = base + (c >> 3) * 8192 + (((c & 7) ^ (row & 7)) << 4);
          asm volatile("stmatrix.sync.aligned.m8n8.x4.shared.b16 [%0], {%1, %2, %3, %4};" ::"r"(addr), "r"(r0), "r"(r1), "r"(r2), "r"(r3) : "memory");
        }
      }
      fence_proxy_async_smem();
      named_bar_sync(3 + cw, 128);
      if (tid == 0) {
        tma_store_2d(&tmO, smem_u32(sm.ostage) + cw * 16384, head * HD, qt * 128 + cw * 64);
        tma_store_2d(&tmO, smem_u32(sm.ostage) + cw * 16384 + 8192, head * HD + 64, qt * 128 + cw * 64);
        tma_store_commit();
      }
      TI(6);
    }
    if (tid == 0) tma_store_wait<0>();
  }
}

__device__ __forceinline__ float bf16r(float x) { return __bfloat162float(__float2bfloat16_rn(x)); }

__global__ void __launch_bounds__(256) ln_kernel(const bf16* __restrict__ x, bf16* __restrict__ xn) {
  const int row = blockIdx.x * 8 + (threadIdx.x >> 5);
  const int lane = threadIdx.x & 31;
  const uint4* src = reinterpret_cast<const uint4*>(x + (size_t)row * DM) + lane * 2;
  uint4 v0 = src[0], v1 = src[1];
  float f[16];
  const uint32_t w[8] = {v0.x, v0.y, v0.z, v0.w, v1.x, v1.y, v1.z, v1.w};
#pragma unroll
  for (int i = 0; i < 8; i++) { f[2 * i] = __uint_as_float(w[i] << 16); f[2 * i + 1] = __uint_as_float(w[i] & 0xffff0000u); }
  float s = 0.f;
#pragma unroll
  for (int i = 0; i < 16; i++) s += f[i];
#pragma unroll
  for (int o = 16; o > 0; o >>= 1) s += __shfl_xor_sync(0xffffffffu, s, o);
  const float mean = s * (1.f / DM);
  float ss = 0.f;
#pragma unroll
  for (int i = 0; i < 16; i++) { float d = f[i] - mean; ss += d * d; }
#pragma unroll
  for (int o = 16; o > 0; o >>= 1) ss += __shfl_xor_sync(0xffffffffu, ss, o);
  const float mb = bf16r(mean);
  const float vb = bf16r(ss * (1.f / DM));
  const float den = bf16r(sqrtf(bf16r(vb + 1e-5f)));
  uint32_t o8[8];
#pragma unroll
  for (int i = 0; i < 8; i++) {
    float a = bf16r(f[2 * i] - mb) / den, b = bf16r(f[2 * i + 1] - mb) / den;
    o8[i] = pack_bf16(a, b);
  }
  uint4* dst = reinterpret_cast<uint4*>(xn + (size_t)row * DM) + lane * 2;
  dst[0] = make_uint4(o8[0], o8[1], o8[2], o8[3]);
  dst[1] = make_uint4(o8[4], o8[5], o8[6], o8[7]);
}

#define PT(ev) do {} while (0)
constexpr int PJ_ST = 12;
constexpr int PJ_NT = 110;
constexpr int PJ_UNITS = 8 * PJ_NT;
struct ProjSmem {
  uint8_t ring[PJ_ST][16384];
  uint8_t ostage[2][16384];
  uint64_t full[PJ_ST], empty[PJ_ST];
  uint64_t ord[2];
};
constexpr int PJ_SMEM_BYTES = sizeof(ProjSmem) + 1024;
struct ProjParams {
  CUtensorMap a[2];
  CUtensorMap b[4];
  CUtensorMap o[4];
};

__device__ __forceinline__ void proj_decode(int u, int& p, int& asrc, int& bm, int& ncol) {
  p = u / PJ_NT;
  int t = u - p * PJ_NT;
  if (t < 64) { asrc = 0; bm = t >> 5; ncol = (t & 31) * 128; }
  else if (t < 96) { asrc = 1; bm = 2; ncol = (t - 64) * 128; }
  else { asrc = 1; bm = 3; ncol = (t - 96) * 128; }
}

__global__ void __cluster_dims__(2, 1, 1) __launch_bounds__(384, 1)
proj_kernel(const __grid_constant__ ProjParams prm) {
  extern __shared__ uint8_t smem_raw[];
  ProjSmem& sm = *reinterpret_cast<ProjSmem*>((reinterpret_cast<uintptr_t>(smem_raw) + 1023) & ~uintptr_t(1023));
  const int wg = threadIdx.x >> 7;
  const uint32_t rank = cluster_ctarank();
  const int cl = blockIdx.x >> 1;
  const int ncl = gridDim.x >> 1;
  const int u0 = (int)(((long long)cl * PJ_UNITS) / ncl), u1 = (int)(((long long)(cl + 1) * PJ_UNITS) / ncl);

  if (threadIdx.x == 0) {
    for (int s = 0; s < PJ_ST; s++) { mbar_init(smem_u32(&sm.full[s]), 1); mbar_init(smem_u32(&sm.empty[s]), 16); }
    mbar_init(smem_u32(&sm.ord[0]), 4); mbar_init(smem_u32(&sm.ord[1]), 4);
    fence_barrier_init();
  }
  __syncthreads();
  cluster_sync_all();

  if (wg == 0) {
    reg_dealloc<40>();
    if (threadIdx.x == 0) {
      int st = 0; uint32_t ph = 0; int prev_key = -1;
      for (int u = u0; u < u1; u++) {
        int p, asrc, bm, ncol; proj_decode(u, p, asrc, bm, ncol);
        const int key = p * 2 + asrc;
        if (key != prev_key) {
          prev_key = key;
          for (int c = 0; c < 8; c++) {
            mbar_wait(smem_u32(&sm.empty[st]), ph ^ 1);
            mbar_expect_tx(smem_u32(&sm.full[st]), 16384);
            tma_load_2d(smem_u32(sm.ring[st]), &prm.a[asrc], smem_u32(&sm.full[st]), c * 64, (2 * p + rank) * 128);
            if (++st == PJ_ST) { st = 0; ph ^= 1; }
          }
        }
        for (int c = 0; c < 8; c++) {
          mbar_wait(smem_u32(&sm.empty[st]), ph ^ 1);
          mbar_expect_tx(smem_u32(&sm.full[st]), 16384);
          tma_load_2d_mc(smem_u32(sm.ring[st]) + rank * 8192, &prm.b[bm], smem_u32(&sm.full[st]), ncol + rank * 64, c * 64, (uint16_t)3);
          if (++st == PJ_ST) { st = 0; ph ^= 1; }
        }
      }
    }
  } else {
    reg_alloc<232>();
    const int cw = __shfl_sync(0xffffffffu, wg - 1, 0);
    const int tid = threadIdx.x & 127;
    const int warp = tid >> 5, lane = tid & 31;
    const uint32_t peer = rank ^ 1;
    int st = 0; uint32_t ph = 0; int prev_key = -1;
    uint32_t a[32][4];
    float acc[64];
    const uint64_t b_desc = make_desc(smem_u32(sm.ring[0]), 8192, 1024);
    auto release = [&](int s) {
      if (lane == 0) mbar_arrive(smem_u32(&sm.empty[s]));
      else if (lane == 1) mbar_arrive_cluster(smem_u32(&sm.empty[s]), peer);
    };
    for (int u = u0; u < u1; u++) {
      int p, asrc, bm, ncol; proj_decode(u, p, asrc, bm, ncol);
      const int key = p * 2 + asrc;
      PT(0);
      if (key != prev_key) {
        prev_key = key;
        const int mi = lane >> 3;
        const int row = cw * 64 + warp * 16 + (lane & 7) + (mi & 1) * 8;
#pragma unroll
        for (int c = 0; c < 8; c++) {
          mbar_wait(smem_u32(&sm.full[st]), ph);
          const uint32_t base = smem_u32(sm.ring[st]) + row * 128;
#pragma unroll
          for (int ks = 0; ks < 4; ks++) {
            const int ch = 2 * ks + (mi >> 1);
            const uint32_t addr = base + ((ch ^ (row & 7)) << 4);
            asm volatile("ldmatrix.sync.aligned.m8n8.x4.shared.b16 {%0, %1, %2, %3}, [%4];"
                         : "=r"(a[4 * c + ks][0]), "=r"(a[4 * c + ks][1]), "=r"(a[4 * c + ks][2]), "=r"(a[4 * c + ks][3]) : "r"(addr) : "memory");
          }
          __syncwarp();
          release(st);
          if (++st == PJ_ST) { st = 0; ph ^= 1; }
        }
      }
      int prev_st = 0;
      PT(1);
      mbar_wait(smem_u32(&sm.ord[cw]), ((u - u0) & 1) ^ (cw ^ 1));
      PT(2);
#pragma unroll
      for (int c = 0; c < 8; c++) {
        mbar_wait(smem_u32(&sm.full[st]), ph);
        const uint64_t bd = b_desc + (uint32_t)(st * (16384 >> 4));
        wgmma_fence();
#pragma unroll
        for (int ks = 0; ks < 4; ks++)
          wgmma_m64n128k16_rs<1>(acc, a[4 * c + ks][0], a[4 * c + ks][1], a[4 * c + ks][2], a[4 * c + ks][3], bd + (ks * 2048 >> 4), (c | ks) != 0);
        wgmma_commit();
        if (c > 0) { wgmma_wait<1>(); release(prev_st); }
        prev_st = st;
        if (++st == PJ_ST) { st = 0; ph ^= 1; }
      }
      PT(3);
      if (lane == 0) mbar_arrive(smem_u32(&sm.ord[cw ^ 1]));
      wgmma_wait<0>();
      reg_fence(acc);
      release(prev_st);
      PT(4);
      if (tid == 0) tma_store_wait_read<0>();
      named_bar_sync(1 + cw, 128);
      {
        const int mi = lane >> 3;
        const int row = warp * 16 + (lane & 7) + (mi & 1) * 8;
        const uint32_t base = smem_u32(sm.ostage[cw]) + row * 128;
        const bool relu = (bm == 3);
#pragma unroll
        for (int jj = 0; jj < 8; jj++) {
          float v[8];
#pragma unroll
          for (int e = 0; e < 8; e++) v[e] = relu ? fmaxf(acc[8 * jj + e], 0.f) : acc[8 * jj + e];
          const int c = 2 * jj + (mi >> 1);
          const uint32_t addr = base + (c >> 3) * 8192 + (((c & 7) ^ (row & 7)) << 4);
          asm volatile("stmatrix.sync.aligned.m8n8.x4.shared.b16 [%0], {%1, %2, %3, %4};" ::"r"(addr), "r"(pack_bf16(v[0], v[1])),
                       "r"(pack_bf16(v[2], v[3])), "r"(pack_bf16(v[4], v[5])), "r"(pack_bf16(v[6], v[7])) : "memory");
        }
      }
      fence_proxy_async_smem();
      named_bar_sync(1 + cw, 128);
      if (tid == 0) {
        const int orow = (2 * p + rank) * 128 + cw * 64;
        tma_store_2d(&prm.o[bm], smem_u32(sm.ostage[cw]), ncol, orow);
        tma_store_2d(&prm.o[bm], smem_u32(sm.ostage[cw]) + 8192, ncol + 64, orow);
        tma_store_commit();
      }
      PT(5);
    }
    if (tid == 0) tma_store_wait<0>();
  }
  __syncthreads();
  cluster_sync_all();
}

constexpr int FN_ST = 4;
constexpr int FN_KB_Y = DFF / 64;
constexpr int FN_KB = FN_KB_Y + HDT / 64;
constexpr int FN_KPS = FN_KB / 4;
struct FinSmem {
  uint8_t a[FN_ST][16384];
  uint8_t b[FN_ST][32768];
  uint64_t full[FN_ST], empty[FN_ST];
};
constexpr int FN_SMEM_BYTES = sizeof(FinSmem) + 1024;
struct FinParams {
  CUtensorMap a[2];
  CUtensorMap b[2];
};
__device__ float g_accS[SEQ * DM];
__device__ float g_accY[SEQ * DM];
__device__ unsigned int g_fin_cnt[32], g_fin_done[32];

__device__ __forceinline__ void red_add_v2(float* p, float a, float b) {
  asm volatile("red.global.add.v2.f32 [%0], {%1, %2};" ::"l"(p), "f"(a), "f"(b) : "memory");
}

__global__ void __cluster_dims__(2, 1, 1) __launch_bounds__(384, 1)
fin_kernel(const __grid_constant__ FinParams prm, const bf16* __restrict__ x, bf16* __restrict__ out) {
  extern __shared__ uint8_t smem_raw[];
  FinSmem& sm = *reinterpret_cast<FinSmem*>((reinterpret_cast<uintptr_t>(smem_raw) + 1023) & ~uintptr_t(1023));
  const int wg = threadIdx.x >> 7;
  const uint32_t rank = cluster_ctarank();
  const int cl = blockIdx.x >> 1;
  const int ksl = cl & 3, tp = cl >> 2;
  const int mblk = (tp >> 1) * 2 + rank, nhalf = tp & 1;
  const int kb0 = ksl * FN_KPS;

  if (threadIdx.x == 0) {
    for (int s = 0; s < FN_ST; s++) { mbar_init(smem_u32(&sm.full[s]), 1); mbar_init(smem_u32(&sm.empty[s]), 16); }
    fence_barrier_init();
  }
  __syncthreads();
  cluster_sync_all();

  if (wg == 0) {
    reg_dealloc<40>();
    if (threadIdx.x == 0) {
      int st = 0; uint32_t ph = 0;
      for (int i = 0; i < FN_KPS; i++) {
        const int kb = kb0 + i;
        const int src = kb < FN_KB_Y ? 0 : 1;
        const int kc = (src ? kb - FN_KB_Y : kb) * 64;
        mbar_wait(smem_u32(&sm.empty[st]), ph ^ 1);
        mbar_expect_tx(smem_u32(&sm.full[st]), 49152);
        tma_load_2d(smem_u32(sm.a[st]), &prm.a[src], smem_u32(&sm.full[st]), kc, mblk * 128);
#pragma unroll
        for (int j = 0; j < 2; j++) {
          const int box = rank * 2 + j;
          tma_load_2d_mc(smem_u32(sm.b[st]) + box * 8192, &prm.b[src], smem_u32(&sm.full[st]), nhalf * 256 + box * 64, kc, (uint16_t)3);
        }
        if (++st == FN_ST) { st = 0; ph ^= 1; }
      }
    }
  } else {
    reg_alloc<232>();
    const int cw = __shfl_sync(0xffffffffu, wg - 1, 0);
    const int tid = threadIdx.x & 127;
    const int warp = tid >> 5, lane = tid & 31;
    const uint32_t peer = rank ^ 1;
    int st = 0; uint32_t ph = 0;
    float acc[128];
    const uint64_t a_desc = make_desc(smem_u32(sm.a[0]) + cw * 8192, 16, 1024);
    const uint64_t b_desc = make_desc(smem_u32(sm.b[0]), 8192, 1024);
    const int row0 = mblk * 128 + cw * 64 + warp * 16 + (lane >> 2);
    const int col0 = nhalf * 256 + 2 * (lane & 3);
    auto flush = [&](float* accbuf) {
#pragma unroll
      for (int j = 0; j < 32; j++) {
        red_add_v2(accbuf + (size_t)row0 * DM + col0 + 8 * j, acc[4 * j], acc[4 * j + 1]);
        red_add_v2(accbuf + (size_t)(row0 + 8) * DM + col0 + 8 * j, acc[4 * j + 2], acc[4 * j + 3]);
      }
    };
    int prev_st = -1;
    bool fresh = true;
    for (int i = 0; i < FN_KPS; i++) {
      const int kb = kb0 + i;
      if (kb == FN_KB_Y && i > 0) {
        wgmma_wait<0>();
        reg_fence(acc);
        if (lane == 0) mbar_arrive(smem_u32(&sm.empty[prev_st]));
        else if (lane == 1) mbar_arrive_cluster(smem_u32(&sm.empty[prev_st]), peer);
        prev_st = -1;
        flush(g_accY);
        fresh = true;
      }
      mbar_wait(smem_u32(&sm.full[st]), ph);
      const uint64_t ad = a_desc + (uint32_t)(st * (16384 >> 4));
      const uint64_t bd = b_desc + (uint32_t)(st * (32768 >> 4));
      wgmma_fence();
#pragma unroll
      for (int ks = 0; ks < 4; ks++)
        wgmma_m64n256k16_ss<1>(acc, ad + (ks * 32 >> 4), bd + (ks * 2048 >> 4), !(fresh && ks == 0));
      wgmma_commit();
      fresh = false;
      if (prev_st >= 0) {
        wgmma_wait<1>();
        if (lane == 0) mbar_arrive(smem_u32(&sm.empty[prev_st]));
        else if (lane == 1) mbar_arrive_cluster(smem_u32(&sm.empty[prev_st]), peer);
      }
      prev_st = st;
      if (++st == FN_ST) { st = 0; ph ^= 1; }
    }
    wgmma_wait<0>();
    reg_fence(acc);
    if (lane == 0) mbar_arrive(smem_u32(&sm.empty[prev_st]));
    else if (lane == 1) mbar_arrive_cluster(smem_u32(&sm.empty[prev_st]), peer);
    flush((kb0 + FN_KPS - 1) < FN_KB_Y ? g_accY : g_accS);
    __threadfence();
    named_bar_sync(1, 256);
    const int tile = mblk * 2 + nhalf;
    if (threadIdx.x == 128) {
      atomicAdd(&g_fin_cnt[tile], 1u);
      unsigned int v;
      do { asm volatile("ld.acquire.gpu.global.u32 %0, [%1];" : "=r"(v) : "l"(&g_fin_cnt[tile]) : "memory"); } while (v < 4u);
    }
    named_bar_sync(1, 256);
    {
      const int t = threadIdx.x - 128;
#pragma unroll
      for (int it = 0; it < 8; it++) {
        const int idx = it * 256 + t;
        const int r = idx >> 6, c4 = idx & 63;
        const size_t off = (size_t)(mblk * 128 + ksl * 32 + r) * DM + nhalf * 256 + c4 * 4;
        float4 sv = __ldcg(reinterpret_cast<const float4*>(g_accS + off));
        float4 yv = __ldcg(reinterpret_cast<const float4*>(g_accY + off));
        *reinterpret_cast<float4*>(g_accS + off) = make_float4(0.f, 0.f, 0.f, 0.f);
        *reinterpret_cast<float4*>(g_accY + off) = make_float4(0.f, 0.f, 0.f, 0.f);
        const uint2 xv = *reinterpret_cast<const uint2*>(x + off);
        const float xs[4] = {__uint_as_float(xv.x << 16), __uint_as_float(xv.x & 0xffff0000u), __uint_as_float(xv.y << 16), __uint_as_float(xv.y & 0xffff0000u)};
        const float ss[4] = {sv.x, sv.y, sv.z, sv.w}, ys[4] = {yv.x, yv.y, yv.z, yv.w};
        float o[4];
#pragma unroll
        for (int e = 0; e < 4; e++) {
          const float y = bf16r(ys[e]);
          const float g = bf16r(y / (1.f + __expf(-y)));
          o[e] = xs[e] + bf16r(bf16r(ss[e]) * g);
        }
        *reinterpret_cast<uint2*>(out + off) = make_uint2(pack_bf16(o[0], o[1]), pack_bf16(o[2], o[3]));
      }
    }
    named_bar_sync(1, 256);
    if (threadIdx.x == 128) {
      __threadfence();
      if (atomicAdd(&g_fin_done[tile], 1u) == 3u) { g_fin_cnt[tile] = 0u; g_fin_done[tile] = 0u; __threadfence(); }
    }
  }
  __syncthreads();
  cluster_sync_all();
}

typedef CUresult (*PFN_encodeTiled)(CUtensorMap*, CUtensorMapDataType, cuuint32_t, void*, const cuuint64_t*, const cuuint64_t*,
                                    const cuuint32_t*, const cuuint32_t*, CUtensorMapInterleave, CUtensorMapSwizzle,
                                    CUtensorMapL2promotion, CUtensorMapFloatOOBfill);

PFN_encodeTiled get_encode_fn() {
  static PFN_encodeTiled fn = nullptr;
  if (!fn) {
    void* p = nullptr;
    cudaDriverEntryPointQueryResult qr;
    cudaGetDriverEntryPoint("cuTensorMapEncodeTiled", &p, cudaEnableDefault, &qr);
    fn = (PFN_encodeTiled)p;
  }
  return fn;
}

CUtensorMap make_tmap(const void* ptr, uint64_t rows, uint64_t cols, uint32_t box_rows, uint32_t box_cols) {
  CUtensorMap tm;
  cuuint64_t gd[2] = {cols, rows};
  cuuint64_t gs[1] = {cols * 2};
  cuuint32_t box[2] = {box_cols, box_rows};
  cuuint32_t es[2] = {1, 1};
  get_encode_fn()(&tm, CU_TENSOR_MAP_DATA_TYPE_BFLOAT16, 2, const_cast<void*>(ptr), gd, gs, box, es, CU_TENSOR_MAP_INTERLEAVE_NONE,
                  CU_TENSOR_MAP_SWIZZLE_128B, CU_TENSOR_MAP_L2_PROMOTION_L2_256B, CU_TENSOR_MAP_FLOAT_OOB_FILL_NONE);
  return tm;
}

template <typename T> T* sym_addr(const T& sym) {
  void* p = nullptr;
  cudaGetSymbolAddress(&p, sym);
  return (T*)p;
}

}

extern "C" void kernel_launch(void* const* d_in, const int* in_sizes, int n_in, void* d_out, int out_size) {
  const bf16* x = (const bf16*)d_in[0];
  const bf16* ckv = (const bf16*)d_in[1];
  const bf16* wq = (const bf16*)d_in[2];
  const bf16* wuk = (const bf16*)d_in[3];
  const bf16* wuv = (const bf16*)d_in[4];
  const bf16* wo = (const bf16*)d_in[5];
  const bf16* w1 = (const bf16*)d_in[7];
  const bf16* w2 = (const bf16*)d_in[8];
  bf16* xn = sym_addr(g_xn[0]) ; bf16* q = sym_addr(g_q[0]); bf16* k = sym_addr(g_k[0]); bf16* v = sym_addr(g_v[0]);
  bf16* h = sym_addr(g_h[0]); bf16* ctx = sym_addr(g_ctx[0]);

  ln_kernel<<<SEQ / 8, 256>>>(x, xn);

  ProjParams pp;
  pp.a[0] = make_tmap(ckv, SEQ, DM, 128, 64);
  pp.a[1] = make_tmap(xn, SEQ, DM, 128, 64);
  pp.b[0] = make_tmap(wuk, DM, HDT, 64, 64);
  pp.b[1] = make_tmap(wuv, DM, HDT, 64, 64);
  pp.b[2] = make_tmap(wq, DM, HDT, 64, 64);
  pp.b[3] = make_tmap(w1, DM, DFF, 64, 64);
  pp.o[0] = make_tmap(k, SEQ, HDT, 64, 64);
  pp.o[1] = make_tmap(v, SEQ, HDT, 64, 64);
  pp.o[2] = make_tmap(q, SEQ, HDT, 64, 64);
  pp.o[3] = make_tmap(h, SEQ, DFF, 64, 64);
  cudaFuncSetAttribute(proj_kernel, cudaFuncAttributeMaxDynamicSharedMemorySize, PJ_SMEM_BYTES);
  proj_kernel<<<132, 384, PJ_SMEM_BYTES>>>(pp);

  CUtensorMap tmQ = make_tmap(q, SEQ, HDT, 128, 64);
  CUtensorMap tmK = make_tmap(k, SEQ, HDT, 128, 64);
  CUtensorMap tmV = make_tmap(v, SEQ, HDT, 128, 64);
  CUtensorMap tmO = make_tmap(ctx, SEQ, HDT, 64, 64);
  cudaFuncSetAttribute(attn_kernel, cudaFuncAttributeMaxDynamicSharedMemorySize, ATT_SMEM_BYTES);
  attn_kernel<<<128, 384, ATT_SMEM_BYTES>>>(tmQ, tmK, tmV, tmO);

  FinParams fp;
  fp.a[0] = make_tmap(h, SEQ, DFF, 128, 64);
  fp.a[1] = make_tmap(ctx, SEQ, HDT, 128, 64);
  fp.b[0] = make_tmap(w2, DFF, DM, 64, 64);
  fp.b[1] = make_tmap(wo, HDT, DM, 64, 64);
  cudaFuncSetAttribute(fin_kernel, cudaFuncAttributeMaxDynamicSharedMemorySize, FN_SMEM_BYTES);
  fin_kernel<<<128, 384, FN_SMEM_BYTES>>>(fp, x, (bf16*)d_out);
}
```

```cpp
#include <cuda_runtime.h>
#include <cuda_bf16.h>
#include <cuda.h>
#include <stdint.h>

typedef __nv_bfloat16 bf16;

namespace {

constexpr int SEQ = 2048;
constexpr int DM  = 512;
constexpr int NH  = 32;
constexpr int HD  = 128;
constexpr int HDT = NH * HD;
constexpr int DFF = 1792;

__device__ __align__(1024) bf16 g_xn[SEQ * DM];
__device__ __align__(1024) bf16 g_q[SEQ * HDT];
__device__ __align__(1024) bf16 g_k[SEQ * HDT];
__device__ __align__(1024) bf16 g_v[SEQ * HDT];
__device__ __align__(1024) bf16 g_h[SEQ * DFF];
__device__ __align__(1024) bf16 g_ctx[SEQ * HDT];

__device__ __forceinline__ uint32_t smem_u32(const void* p) { return (uint32_t)__cvta_generic_to_shared(p); }

__device__ __forceinline__ void mbar_init(uint32_t bar, uint32_t cnt) {
  asm volatile("mbarrier.init.shared::cta.b64 [%0], %1;" ::"r"(bar), "r"(cnt));
}
__device__ __forceinline__ void mbar_expect_tx(uint32_t bar, uint32_t bytes) {
  asm volatile("mbarrier.arrive.expect_tx.shared::cta.b64 _, [%0], %1;" ::"r"(bar), "r"(bytes) : "memory");
}
__device__ __forceinline__ void mbar_arrive(uint32_t bar) {
  asm volatile("mbarrier.arrive.shared::cta.b64 _, [%0];" ::"r"(bar) : "memory");
}
__device__ __forceinline__ void mbar_arrive_cluster(uint32_t bar, uint32_t cta) {
  asm volatile("{\n.reg .b32 ra;\nmapa.shared::cluster.u32 ra, %0, %1;\nmbarrier.arrive.shared::cluster.b64 _, [ra];\n}\n" ::"r"(bar), "r"(cta) : "memory");
}
__device__ __forceinline__ bool mbar_try_wait(uint32_t bar, uint32_t parity) {
  uint32_t ok;
  asm volatile("{\n.reg .pred p;\nmbarrier.try_wait.parity.shared::cta.b64 p, [%1], %2;\nselp.u32 %0, 1, 0, p;\n}\n" : "=r"(ok) : "r"(bar), "r"(parity) : "memory");
  return ok != 0;
}
__device__ __forceinline__ void mbar_wait(uint32_t bar, uint32_t parity) {
  while (!mbar_try_wait(bar, parity)) {}
}
__device__ __forceinline__ void fence_barrier_init() { asm volatile("fence.mbarrier_init.release.cluster;" ::: "memory"); }
__device__ __forceinline__ void fence_proxy_async() { asm volatile("fence.proxy.async;" ::: "memory"); }
__device__ __forceinline__ void fence_proxy_async_smem() { asm volatile("fence.proxy.async.shared::cta;" ::: "memory"); }

__device__ __forceinline__ void tma_load_2d(uint32_t dst, const CUtensorMap* tm, uint32_t bar, int c0, int c1) {
  asm volatile("cp.async.bulk.tensor.2d.shared::cluster.global.mbarrier::complete_tx::bytes [%0], [%1, {%3, %4}], [%2];"
               ::"r"(dst), "l"(tm), "r"(bar), "r"(c0), "r"(c1) : "memory");
}
__device__ __forceinline__ void tma_load_2d_mc(uint32_t dst, const CUtensorMap* tm, uint32_t bar, int c0, int c1, uint16_t mask) {
  asm volatile("cp.async.bulk.tensor.2d.shared::cluster.global.mbarrier::complete_tx::bytes.multicast::cluster [%0], [%1, {%3, %4}], [%2], %5;"
               ::"r"(dst), "l"(tm), "r"(bar), "r"(c0), "r"(c1), "h"(mask) : "memory");
}
__device__ __forceinline__ void tma_store_2d(const CUtensorMap* tm, uint32_t src, int c0, int c1) {
  asm volatile("cp.async.bulk.tensor.2d.global.shared::cta.bulk_group [%0, {%2, %3}], [%1];"
               ::"l"(tm), "r"(src), "r"(c0), "r"(c1) : "memory");
}
__device__ __forceinline__ void tma_store_commit() { asm volatile("cp.async.bulk.commit_group;" ::: "memory"); }
template <int N> __device__ __forceinline__ void tma_store_wait_read() { asm volatile("cp.async.bulk.wait_group.read %0;" ::"n"(N) : "memory"); }
template <int N> __device__ __forceinline__ void tma_store_wait() { asm volatile("cp.async.bulk.wait_group %0;" ::"n"(N) : "memory"); }
__device__ __forceinline__ void prefetch_tmap(const CUtensorMap* tm) { asm volatile("prefetch.tensormap [%0];" ::"l"(tm) : "memory"); }

__device__ __forceinline__ void named_bar_sync(int id, int nthreads) { asm volatile("bar.sync %0, %1;" ::"r"(id), "r"(nthreads) : "memory"); }
__device__ __forceinline__ void named_bar_arrive(int id, int nthreads) { asm volatile("bar.arrive %0, %1;" ::"r"(id), "r"(nthreads) : "memory"); }

__device__ __forceinline__ uint32_t cluster_ctarank() { uint32_t r; asm volatile("mov.u32 %0, %%cluster_ctarank;" : "=r"(r)); return r; }
__device__ __forceinline__ void cluster_sync_all() { asm volatile("barrier.cluster.arrive.release.aligned;\nbarrier.cluster.wait.acquire.aligned;" ::: "memory"); }

template <int R> __device__ __forceinline__ void reg_alloc() { asm volatile("setmaxnreg.inc.sync.aligned.u32 %0;" ::"n"(R)); }
template <int R> __device__ __forceinline__ void reg_dealloc() { asm volatile("setmaxnreg.dec.sync.aligned.u32 %0;" ::"n"(R)); }

__device__ __forceinline__ void wgmma_fence() { asm volatile("wgmma.fence.sync.aligned;" ::: "memory"); }
__device__ __forceinline__ void wgmma_commit() { asm volatile("wgmma.commit_group.sync.aligned;" ::: "memory"); }
template <int N> __device__ __forceinline__ void wgmma_wait() { asm volatile("wgmma.wait_group.sync.aligned %0;" ::"n"(N) : "memory"); }

__device__ __forceinline__ uint64_t make_desc(uint32_t saddr, uint32_t lbo, uint32_t sbo) {
  uint64_t d = 0;
  d |= (uint64_t)((saddr & 0x3FFFF) >> 4);
  d |= (uint64_t)((lbo & 0x3FFFF) >> 4) << 16;
  d |= (uint64_t)((sbo & 0x3FFFF) >> 4) << 32;
  d |= (uint64_t)1 << 62;
  return d;
}

__device__ __forceinline__ uint32_t pack_bf16(float lo, float hi) {
  uint32_t r;
  asm("cvt.rn.bf16x2.f32 %0, %1, %2;" : "=r"(r) : "f"(hi), "f"(lo));
  return r;
}
__device__ __forceinline__ float ex2(float x) { float y; asm("ex2.approx.ftz.f32 %0, %1;" : "=f"(y) : "f"(x)); return y; }

template<int TB> __device__ __forceinline__ void wgmma_m64n128k16_ss(float (&d)[64], uint64_t da, uint64_t db, int scale_d) {
  asm volatile("{\n.reg .pred p;\nsetp.ne.b32 p, %66, 0;\nwgmma.mma_async.sync.aligned.m64n128k16.f32.bf16.bf16 {%0, %1, %2, %3, %4, %5, %6, %7, %8, %9, %10, %11, %12, %13, %14, %15, %16, %17, %18, %19, %20, %21, %22, %23, %24, %25, %26, %27, %28, %29, %30, %31, %32, %33, %34, %35, %36, %37, %38, %39, %40, %41, %42, %43, %44, %45, %46, %47, %48, %49, %50, %51, %52, %53, %54, %55, %56, %57, %58, %59, %60, %61, %62, %63}, %64, %65, p, 1, 1, 0, %67;\n}\n"
    : "+f"(d[0]), "+f"(d[1]), "+f"(d[2]), "+f"(d[3]), "+f"(d[4]), "+f"(d[5]), "+f"(d[6]), "+f"(d[7]), "+f"(d[8]), "+f"(d[9]), "+f"(d[10]), "+f"(d[11]), "+f"(d[12]), "+f"(d[13]), "+f"(d[14]), "+f"(d[15]), "+f"(d[16]), "+f"(d[17]), "+f"(d[18]), "+f"(d[19]), "+f"(d[20]), "+f"(d[21]), "+f"(d[22]), "+f"(d[23]), "+f"(d[24]), "+f"(d[25]), "+f"(d[26]), "+f"(d[27]), "+f"(d[28]), "+f"(d[29]), "+f"(d[30]), "+f"(d[31]), "+f"(d[32]), "+f"(d[33]), "+f"(d[34]), "+f"(d[35]), "+f"(d[36]), "+f"(d[37]), "+f"(d[38]), "+f"(d[39]), "+f"(d[40]), "+f"(d[41]), "+f"(d[42]), "+f"(d[43]), "+f"(d[44]), "+f"(d[45]), "+f"(d[46]), "+f"(d[47]), "+f"(d[48]), "+f"(d[49]), "+f"(d[50]), "+f"(d[51]), "+f"(d[52]), "+f"(d[53]), "+f"(d[54]), "+f"(d[55]), "+f"(d[56]), "+f"(d[57]), "+f"(d[58]), "+f"(d[59]), "+f"(d[60]), "+f"(d[61]), "+f"(d[62]), "+f"(d[63])
    : "l"(da), "l"(db), "r"(scale_d), "n"(TB));
}

template<int TB> __device__ __forceinline__ void wgmma_m64n128k16_rs(float (&d)[64], uint32_t a0, uint32_t a1, uint32_t a2, uint32_t a3, uint64_t db, int scale_d) {
  asm volatile("{\n.reg .pred p;\nsetp.ne.b32 p, %69, 0;\nwgmma.mma_async.sync.aligned.m64n128k16.f32.bf16.bf16 {%0, %1, %2, %3, %4, %5, %6, %7, %8, %9, %10, %11, %12, %13, %14, %15, %16, %17, %18, %19, %20, %21, %22, %23, %24, %25, %26, %27, %28, %29, %30, %31, %32, %33, %34, %35, %36, %37, %38, %39, %40, %41, %42, %43, %44, %45, %46, %47, %48, %49, %50, %51, %52, %53, %54, %55, %56, %57, %58, %59, %60, %61, %62, %63}, {%64, %65, %66, %67}, %68, p, 1, 1, %70;\n}\n"
    : "+f"(d[0]), "+f"(d[1]), "+f"(d[2]), "+f"(d[3]), "+f"(d[4]), "+f"(d[5]), "+f"(d[6]), "+f"(d[7]), "+f"(d[8]), "+f"(d[9]), "+f"(d[10]), "+f"(d[11]), "+f"(d[12]), "+f"(d[13]), "+f"(d[14]), "+f"(d[15]), "+f"(d[16]), "+f"(d[17]), "+f"(d[18]), "+f"(d[19]), "+f"(d[20]), "+f"(d[21]), "+f"(d[22]), "+f"(d[23]), "+f"(d[24]), "+f"(d[25]), "+f"(d[26]), "+f"(d[27]), "+f"(d[28]), "+f"(d[29]), "+f"(d[30]), "+f"(d[31]), "+f"(d[32]), "+f"(d[33]), "+f"(d[34]), "+f"(d[35]), "+f"(d[36]), "+f"(d[37]), "+f"(d[38]), "+f"(d[39]), "+f"(d[40]), "+f"(d[41]), "+f"(d[42]), "+f"(d[43]), "+f"(d[44]), "+f"(d[45]), "+f"(d[46]), "+f"(d[47]), "+f"(d[48]), "+f"(d[49]), "+f"(d[50]), "+f"(d[51]), "+f"(d[52]), "+f"(d[53]), "+f"(d[54]), "+f"(d[55]), "+f"(d[56]), "+f"(d[57]), "+f"(d[58]), "+f"(d[59]), "+f"(d[60]), "+f"(d[61]), "+f"(d[62]), "+f"(d[63])
    : "r"(a0), "r"(a1), "r"(a2), "r"(a3), "l"(db), "r"(scale_d), "n"(TB));
}

template<int TB> __device__ __forceinline__ void wgmma_m64n256k16_ss(float (&d)[128], uint64_t da, uint64_t db, int scale_d) {
  asm volatile("{\n.reg .pred p;\nsetp.ne.b32 p, %130, 0;\nwgmma.mma_async.sync.aligned.m64n256k16.f32.bf16.bf16 {%0, %1, %2, %3, %4, %5, %6, %7, %8, %9, %10, %11, %12, %13, %14, %15, %16, %17, %18, %19, %20, %21, %22, %23, %24, %25, %26, %27, %28, %29, %30, %31, %32, %33, %34, %35, %36, %37, %38, %39, %40, %41, %42, %43, %44, %45, %46, %47, %48, %49, %50, %51, %52, %53, %54, %55, %56, %57, %58, %59, %60, %61, %62, %63, %64, %65, %66, %67, %68, %69, %70, %71, %72, %73, %74, %75, %76, %77, %78, %79, %80, %81, %82, %83, %84, %85, %86, %87, %88, %89, %90, %91, %92, %93, %94, %95, %96, %97, %98, %99, %100, %101, %102, %103, %104, %105, %106, %107, %108, %109, %110, %111, %112, %113, %114, %115, %116, %117, %118, %119, %120, %121, %122, %123, %124, %125, %126, %127}, %128, %129, p, 1, 1, 0, %131;\n}\n"
    : "+f"(d[0]), "+f"(d[1]), "+f"(d[2]), "+f"(d[3]), "+f"(d[4]), "+f"(d[5]), "+f"(d[6]), "+f"(d[7]), "+f"(d[8]), "+f"(d[9]), "+f"(d[10]), "+f"(d[11]), "+f"(d[12]), "+f"(d[13]), "+f"(d[14]), "+f"(d[15]), "+f"(d[16]), "+f"(d[17]), "+f"(d[18]), "+f"(d[19]), "+f"(d[20]), "+f"(d[21]), "+f"(d[22]), "+f"(d[23]), "+f"(d[24]), "+f"(d[25]), "+f"(d[26]), "+f"(d[27]), "+f"(d[28]), "+f"(d[29]), "+f"(d[30]), "+f"(d[31]), "+f"(d[32]), "+f"(d[33]), "+f"(d[34]), "+f"(d[35]), "+f"(d[36]), "+f"(d[37]), "+f"(d[38]), "+f"(d[39]), "+f"(d[40]), "+f"(d[41]), "+f"(d[42]), "+f"(d[43]), "+f"(d[44]), "+f"(d[45]), "+f"(d[46]), "+f"(d[47]), "+f"(d[48]), "+f"(d[49]), "+f"(d[50]), "+f"(d[51]), "+f"(d[52]), "+f"(d[53]), "+f"(d[54]), "+f"(d[55]), "+f"(d[56]), "+f"(d[57]), "+f"(d[58]), "+f"(d[59]), "+f"(d[60]), "+f"(d[61]), "+f"(d[62]), "+f"(d[63]), "+f"(d[64]), "+f"(d[65]), "+f"(d[66]), "+f"(d[67]), "+f"(d[68]), "+f"(d[69]), "+f"(d[70]), "+f"(d[71]), "+f"(d[72]), "+f"(d[73]), "+f"(d[74]), "+f"(d[75]), "+f"(d[76]), "+f"(d[77]), "+f"(d[78]), "+f"(d[79]), "+f"(d[80]), "+f"(d[81]), "+f"(d[82]), "+f"(d[83]), "+f"(d[84]), "+f"(d[85]), "+f"(d[86]), "+f"(d[87]), "+f"(d[88]), "+f"(d[89]), "+f"(d[90]), "+f"(d[91]), "+f"(d[92]), "+f"(d[93]), "+f"(d[94]), "+f"(d[95]), "+f"(d[96]), "+f"(d[97]), "+f"(d[98]), "+f"(d[99]), "+f"(d[100]), "+f"(d[101]), "+f"(d[102]), "+f"(d[103]), "+f"(d[104]), "+f"(d[105]), "+f"(d[106]), "+f"(d[107]), "+f"(d[108]), "+f"(d[109]), "+f"(d[110]), "+f"(d[111]), "+f"(d[112]), "+f"(d[113]), "+f"(d[114]), "+f"(d[115]), "+f"(d[116]), "+f"(d[117]), "+f"(d[118]), "+f"(d[119]), "+f"(d[120]), "+f"(d[121]), "+f"(d[122]), "+f"(d[123]), "+f"(d[124]), "+f"(d[125]), "+f"(d[126]), "+f"(d[127])
    : "l"(da), "l"(db), "r"(scale_d), "n"(TB));
}

template<int TB> __device__ __forceinline__ void wgmma_m64n64k16_ss(float (&d)[32], uint64_t da, uint64_t db, int scale_d) {
  asm volatile("{\n.reg .pred p;\nsetp.ne.b32 p, %34, 0;\nwgmma.mma_async.sync.aligned.m64n64k16.f32.bf16.bf16 {%0, %1, %2, %3, %4, %5, %6, %7, %8, %9, %10, %11, %12, %13, %14, %15, %16, %17, %18, %19, %20, %21, %22, %23, %24, %25, %26, %27, %28, %29, %30, %31}, %32, %33, p, 1, 1, 0, %35;\n}\n"
    : "+f"(d[0]), "+f"(d[1]), "+f"(d[2]), "+f"(d[3]), "+f"(d[4]), "+f"(d[5]), "+f"(d[6]), "+f"(d[7]), "+f"(d[8]), "+f"(d[9]), "+f"(d[10]), "+f"(d[11]), "+f"(d[12]), "+f"(d[13]), "+f"(d[14]), "+f"(d[15]), "+f"(d[16]), "+f"(d[17]), "+f"(d[18]), "+f"(d[19]), "+f"(d[20]), "+f"(d[21]), "+f"(d[22]), "+f"(d[23]), "+f"(d[24]), "+f"(d[25]), "+f"(d[26]), "+f"(d[27]), "+f"(d[28]), "+f"(d[29]), "+f"(d[30]), "+f"(d[31])
    : "l"(da), "l"(db), "r"(scale_d), "n"(TB));
}

template<int TB> __device__ __forceinline__ void wgmma_m64n64k16_rs(float (&d)[32], uint32_t a0, uint32_t a1, uint32_t a2, uint32_t a3, uint64_t db, int scale_d) {
  asm volatile("{\n.reg .pred p;\nsetp.ne.b32 p, %37, 0;\nwgmma.mma_async.sync.aligned.m64n64k16.f32.bf16.bf16 {%0, %1, %2, %3, %4, %5, %6, %7, %8, %9, %10, %11, %12, %13, %14, %15, %16, %17, %18, %19, %20, %21, %22, %23, %24, %25, %26, %27, %28, %29, %30, %31}, {%32, %33, %34, %35}, %36, p, 1, 1, %38;\n}\n"
    : "+f"(d[0]), "+f"(d[1]), "+f"(d[2]), "+f"(d[3]), "+f"(d[4]), "+f"(d[5]), "+f"(d[6]), "+f"(d[7]), "+f"(d[8]), "+f"(d[9]), "+f"(d[10]), "+f"(d[11]), "+f"(d[12]), "+f"(d[13]), "+f"(d[14]), "+f"(d[15]), "+f"(d[16]), "+f"(d[17]), "+f"(d[18]), "+f"(d[19]), "+f"(d[20]), "+f"(d[21]), "+f"(d[22]), "+f"(d[23]), "+f"(d[24]), "+f"(d[25]), "+f"(d[26]), "+f"(d[27]), "+f"(d[28]), "+f"(d[29]), "+f"(d[30]), "+f"(d[31])
    : "r"(a0), "r"(a1), "r"(a2), "r"(a3), "l"(db), "r"(scale_d), "n"(TB));
}

__device__ __forceinline__ void reg_fence(float (&d)[32]) {
  asm volatile("" : "+f"(d[0]), "+f"(d[1]), "+f"(d[2]), "+f"(d[3]), "+f"(d[4]), "+f"(d[5]), "+f"(d[6]), "+f"(d[7]), "+f"(d[8]), "+f"(d[9]), "+f"(d[10]), "+f"(d[11]), "+f"(d[12]), "+f"(d[13]), "+f"(d[14]), "+f"(d[15]), "+f"(d[16]), "+f"(d[17]), "+f"(d[18]), "+f"(d[19]), "+f"(d[20]), "+f"(d[21]), "+f"(d[22]), "+f"(d[23]), "+f"(d[24]), "+f"(d[25]), "+f"(d[26]), "+f"(d[27]), "+f"(d[28]), "+f"(d[29]), "+f"(d[30]), "+f"(d[31]) :: "memory");
}

__device__ __forceinline__ void reg_fence(float (&d)[64]) {
  asm volatile("" : "+f"(d[0]), "+f"(d[1]), "+f"(d[2]), "+f"(d[3]), "+f"(d[4]), "+f"(d[5]), "+f"(d[6]), "+f"(d[7]), "+f"(d[8]), "+f"(d[9]), "+f"(d[10]), "+f"(d[11]), "+f"(d[12]), "+f"(d[13]), "+f"(d[14]), "+f"(d[15]), "+f"(d[16]), "+f"(d[17]), "+f"(d[18]), "+f"(d[19]), "+f"(d[20]), "+f"(d[21]), "+f"(d[22]), "+f"(d[23]), "+f"(d[24]), "+f"(d[25]), "+f"(d[26]), "+f"(d[27]), "+f"(d[28]), "+f"(d[29]), "+f"(d[30]), "+f"(d[31]), "+f"(d[32]), "+f"(d[33]), "+f"(d[34]), "+f"(d[35]), "+f"(d[36]), "+f"(d[37]), "+f"(d[38]), "+f"(d[39]), "+f"(d[40]), "+f"(d[41]), "+f"(d[42]), "+f"(d[43]), "+f"(d[44]), "+f"(d[45]), "+f"(d[46]), "+f"(d[47]), "+f"(d[48]), "+f"(d[49]), "+f"(d[50]), "+f"(d[51]), "+f"(d[52]), "+f"(d[53]), "+f"(d[54]), "+f"(d[55]), "+f"(d[56]), "+f"(d[57]), "+f"(d[58]), "+f"(d[59]), "+f"(d[60]), "+f"(d[61]), "+f"(d[62]), "+f"(d[63]) :: "memory");
}

__device__ __forceinline__ void reg_fence(float (&d)[128]) {
  asm volatile("" : "+f"(d[0]), "+f"(d[1]), "+f"(d[2]), "+f"(d[3]), "+f"(d[4]), "+f"(d[5]), "+f"(d[6]), "+f"(d[7]), "+f"(d[8]), "+f"(d[9]), "+f"(d[10]), "+f"(d[11]), "+f"(d[12]), "+f"(d[13]), "+f"(d[14]), "+f"(d[15]), "+f"(d[16]), "+f"(d[17]), "+f"(d[18]), "+f"(d[19]), "+f"(d[20]), "+f"(d[21]), "+f"(d[22]), "+f"(d[23]), "+f"(d[24]), "+f"(d[25]), "+f"(d[26]), "+f"(d[27]), "+f"(d[28]), "+f"(d[29]), "+f"(d[30]), "+f"(d[31]), "+f"(d[32]), "+f"(d[33]), "+f"(d[34]), "+f"(d[35]), "+f"(d[36]), "+f"(d[37]), "+f"(d[38]), "+f"(d[39]), "+f"(d[40]), "+f"(d[41]), "+f"(d[42]), "+f"(d[43]), "+f"(d[44]), "+f"(d[45]), "+f"(d[46]), "+f"(d[47]), "+f"(d[48]), "+f"(d[49]), "+f"(d[50]), "+f"(d[51]), "+f"(d[52]), "+f"(d[53]), "+f"(d[54]), "+f"(d[55]), "+f"(d[56]), "+f"(d[57]), "+f"(d[58]), "+f"(d[59]), "+f"(d[60]), "+f"(d[61]), "+f"(d[62]), "+f"(d[63]), "+f"(d[64]), "+f"(d[65]), "+f"(d[66]), "+f"(d[67]), "+f"(d[68]), "+f"(d[69]), "+f"(d[70]), "+f"(d[71]), "+f"(d[72]), "+f"(d[73]), "+f"(d[74]), "+f"(d[75]), "+f"(d[76]), "+f"(d[77]), "+f"(d[78]), "+f"(d[79]), "+f"(d[80]), "+f"(d[81]), "+f"(d[82]), "+f"(d[83]), "+f"(d[84]), "+f"(d[85]), "+f"(d[86]), "+f"(d[87]), "+f"(d[88]), "+f"(d[89]), "+f"(d[90]), "+f"(d[91]), "+f"(d[92]), "+f"(d[93]), "+f"(d[94]), "+f"(d[95]), "+f"(d[96]), "+f"(d[97]), "+f"(d[98]), "+f"(d[99]), "+f"(d[100]), "+f"(d[101]), "+f"(d[102]), "+f"(d[103]), "+f"(d[104]), "+f"(d[105]), "+f"(d[106]), "+f"(d[107]), "+f"(d[108]), "+f"(d[109]), "+f"(d[110]), "+f"(d[111]), "+f"(d[112]), "+f"(d[113]), "+f"(d[114]), "+f"(d[115]), "+f"(d[116]), "+f"(d[117]), "+f"(d[118]), "+f"(d[119]), "+f"(d[120]), "+f"(d[121]), "+f"(d[122]), "+f"(d[123]), "+f"(d[124]), "+f"(d[125]), "+f"(d[126]), "+f"(d[127]) :: "memory");
}

#define ATT_PINGPONG 1
#define TR(ev) do {} while (0)
#define TI(ev) do {} while (0)
constexpr int ATT_K_ST = 3, ATT_V_ST = 2;
constexpr int ATT_TILE_BYTES = 128 * 128 * 2;
struct AttnSmem {
  uint8_t q[ATT_TILE_BYTES];
  uint8_t k[ATT_K_ST][ATT_TILE_BYTES];
  uint8_t v[ATT_V_ST][ATT_TILE_BYTES];
  uint8_t ostage[ATT_TILE_BYTES];
  uint64_t q_full, q_empty;
  uint64_t k_full[ATT_K_ST], k_empty[ATT_K_ST], v_full[ATT_V_ST], v_empty[ATT_V_ST];
};
constexpr int ATT_SMEM_BYTES = sizeof(AttnSmem) + 1024;
constexpr int ATT_ITEMS_PER_CTA = 4;

__device__ __forceinline__ void attn_item(int cta, int it, int& head, int& qt) {
  head = 8 * it + (cta >> 4);
  int r = cta & 15;
  qt = (it & 1) ? (15 - r) : r;
}

__global__ void __launch_bounds__(384, 1)
attn_kernel(const __grid_constant__ CUtensorMap tmQ, const __grid_constant__ CUtensorMap tmK,
            const __grid_constant__ CUtensorMap tmV, const __grid_constant__ CUtensorMap tmO) {
  extern __shared__ uint8_t smem_raw[];
  AttnSmem& sm = *reinterpret_cast<AttnSmem*>((reinterpret_cast<uintptr_t>(smem_raw) + 1023) & ~uintptr_t(1023));
  const int wg = threadIdx.x >> 7;
  const int cta = blockIdx.x;

  if (threadIdx.x == 0) {
    mbar_init(smem_u32(&sm.q_full), 1);
    mbar_init(smem_u32(&sm.q_empty), 8);
    for (int s = 0; s < ATT_K_ST; s++) {
      mbar_init(smem_u32(&sm.k_full[s]), 1);
      mbar_init(smem_u32(&sm.k_empty[s]), 8);
    }
    for (int s = 0; s < ATT_V_ST; s++) {
      mbar_init(smem_u32(&sm.v_full[s]), 1);
      mbar_init(smem_u32(&sm.v_empty[s]), 8);
    }
    fence_barrier_init();
  }
  __syncthreads();

  if (wg == 0) {
    reg_dealloc<40>();
    if (threadIdx.x == 0) {
      int kst = 0, vst = 0; uint32_t kph = 0, vph = 0;
      for (int it = 0; it < ATT_ITEMS_PER_CTA; it++) {
        int head, qt; attn_item(cta, it, head, qt);
        mbar_wait(smem_u32(&sm.q_empty), (it & 1) ^ 1);
        mbar_expect_tx(smem_u32(&sm.q_full), ATT_TILE_BYTES);
        tma_load_2d(smem_u32(sm.q), &tmQ, smem_u32(&sm.q_full), head * HD, qt * 128);
        tma_load_2d(smem_u32(sm.q) + 16384, &tmQ, smem_u32(&sm.q_full), head * HD + 64, qt * 128);
        for (int n = qt; n >= 0; --n) {
          mbar_wait(smem_u32(&sm.k_empty[kst]), kph ^ 1);
          mbar_expect_tx(smem_u32(&sm.k_full[kst]), ATT_TILE_BYTES);
          tma_load_2d(smem_u32(sm.k[kst]), &tmK, smem_u32(&sm.k_full[kst]), head * HD, n * 128);
          tma_load_2d(smem_u32(sm.k[kst]) + 16384, &tmK, smem_u32(&sm.k_full[kst]), head * HD + 64, n * 128);
          if (++kst == ATT_K_ST) { kst = 0; kph ^= 1; }
          mbar_wait(smem_u32(&sm.v_empty[vst]), vph ^ 1);
          mbar_expect_tx(smem_u32(&sm.v_full[vst]), ATT_TILE_BYTES);
          tma_load_2d(smem_u32(sm.v[vst]), &tmV, smem_u32(&sm.v_full[vst]), head * HD, n * 128);
          tma_load_2d(smem_u32(sm.v[vst]) + 16384, &tmV, smem_u32(&sm.v_full[vst]), head * HD + 64, n * 128);
          if (++vst == ATT_V_ST) { vst = 0; vph ^= 1; }
        }
      }
    }
  } else {
    reg_alloc<232>();
    const int cw = __shfl_sync(0xffffffffu, wg - 1, 0);
    const int tid = threadIdx.x & 127;
    const int warp = tid >> 5, lane = tid & 31;
    const float sl2 = 0.08838834764831845f * 1.4426950408889634f;
    int kst = 0, vst = 0; uint32_t kph = 0, vph = 0;
    const uint64_t q_desc = make_desc(smem_u32(sm.q) + cw * 8192, 16, 1024);
    const uint64_t k_desc = make_desc(smem_u32(sm.k[0]), 16, 1024);
    const uint64_t v_desc = make_desc(smem_u32(sm.v[0]), 16384, 1024);
    float o[64], s[64];
    uint32_t p[32];
    if (cw == 1) named_bar_arrive(1, 256);
    auto issue_qk = [&]() {
      mbar_wait(smem_u32(&sm.k_full[kst]), kph);
      const uint64_t kd = k_desc + (uint32_t)(kst * (ATT_TILE_BYTES >> 4));
      wgmma_fence();
#pragma unroll
      for (int ks = 0; ks < 8; ks++) {
        const uint32_t off = ((ks >> 2) * 16384 + (ks & 3) * 32) >> 4;
        wgmma_m64n128k16_ss<0>(s, q_desc + off, kd + off, ks > 0);
      }
      wgmma_commit();
    };
    auto issue_pv = [&]() {
      mbar_wait(smem_u32(&sm.v_full[vst]), vph);
      const uint64_t vd = v_desc + (uint32_t)(vst * (ATT_TILE_BYTES >> 4));
      wgmma_fence();
#pragma unroll
      for (int ks = 0; ks < 8; ks++) {
        wgmma_m64n128k16_rs<1>(o, p[4 * ks], p[4 * ks + 1], p[4 * ks + 2], p[4 * ks + 3], vd + (ks * 2048 >> 4), 1);
      }
      wgmma_commit();
    };
    auto release_k = [&]() {
      if (lane == 0) mbar_arrive(smem_u32(&sm.k_empty[kst]));
      if (++kst == ATT_K_ST) { kst = 0; kph ^= 1; }
    };
    auto release_v = [&]() {
      if (lane == 0) mbar_arrive(smem_u32(&sm.v_empty[vst]));
      if (++vst == ATT_V_ST) { vst = 0; vph ^= 1; }
    };
    auto sched_sync = [&]() {
      named_bar_sync(1 + cw, 256);
    };
    auto sched_arrive = [&]() {
      named_bar_arrive(1 + (cw ^ 1), 256);
    };

    for (int it = 0; it < ATT_ITEMS_PER_CTA; it++) {
      int head, qt; attn_item(cta, it, head, qt);
      float m0, m1, l0, l1, a0 = 1.f, a1 = 1.f;
#pragma unroll
      for (int i = 0; i < 64; i++) o[i] = 0.f;
      TI(0);
      mbar_wait(smem_u32(&sm.q_full), it & 1);
      TI(1);
      sched_sync();
      issue_qk();
      sched_arrive();
      wgmma_wait<0>();
      reg_fence(s);
      TI(2);
      release_k();
      if (qt == 0 && lane == 0) mbar_arrive(smem_u32(&sm.q_empty));
      {
        const int r0 = cw * 64 + warp * 16 + (lane >> 2);
#pragma unroll
        for (int j = 0; j < 16; j++) {
          int c = 8 * j + 2 * (lane & 3);
          if (c > r0) s[4 * j] = -INFINITY;
          if (c + 1 > r0) s[4 * j + 1] = -INFINITY;
          if (c > r0 + 8) s[4 * j + 2] = -INFINITY;
          if (c + 1 > r0 + 8) s[4 * j + 3] = -INFINITY;
        }
        float mx0 = fmaxf(s[0], s[1]), mx1 = fmaxf(s[2], s[3]);
#pragma unroll
        for (int j = 1; j < 16; j++) {
          mx0 = fmaxf(mx0, fmaxf(s[4 * j], s[4 * j + 1]));
          mx1 = fmaxf(mx1, fmaxf(s[4 * j + 2], s[4 * j + 3]));
        }
        mx0 = fmaxf(mx0, __shfl_xor_sync(0xffffffffu, mx0, 1));
        mx1 = fmaxf(mx1, __shfl_xor_sync(0xffffffffu, mx1, 1));
        mx0 = fmaxf(mx0, __shfl_xor_sync(0xffffffffu, mx0, 2));
        mx1 = fmaxf(mx1, __shfl_xor_sync(0xffffffffu, mx1, 2));
        m0 = mx0; m1 = mx1;
        const float ms0 = m0 * sl2, ms1 = m1 * sl2;
        l0 = 0.f; l1 = 0.f;
#pragma unroll
        for (int j = 0; j < 16; j++) {
          float p0 = ex2(fmaf(s[4 * j], sl2, -ms0));
          float p1 = ex2(fmaf(s[4 * j + 1], sl2, -ms0));
          float p2 = ex2(fmaf(s[4 * j + 2], sl2, -ms1));
          float p3 = ex2(fmaf(s[4 * j + 3], sl2, -ms1));
          l0 += p0 + p1; l1 += p2 + p3;
          p[2 * j] = pack_bf16(p0, p1);
          p[2 * j + 1] = pack_bf16(p2, p3);
        }
      }
      TI(3);
      for (int n = qt - 1; n >= 0; --n) {
        if (n != qt - 1) {
          TR(6);
          wgmma_wait<0>();
          reg_fence(o);
          TR(7);
          release_v();
#pragma unroll
          for (int j = 0; j < 16; j++) {
            p[2 * j] = pack_bf16(s[4 * j], s[4 * j + 1]);
            p[2 * j + 1] = pack_bf16(s[4 * j + 2], s[4 * j + 3]);
          }
        }
        TR(0);
        sched_sync();
        TR(1);
        issue_qk();
        TR(2);
#pragma unroll
        for (int j = 0; j < 16; j++) {
          o[4 * j] *= a0; o[4 * j + 1] *= a0; o[4 * j + 2] *= a1; o[4 * j + 3] *= a1;
        }
        issue_pv();
        TR(3);
        sched_arrive();
        wgmma_wait<1>();
        reg_fence(s);
        TR(4);
        release_k();
        if (n == 0 && lane == 0) mbar_arrive(smem_u32(&sm.q_empty));
        float mx0 = fmaxf(s[0], s[1]), mx1 = fmaxf(s[2], s[3]);
#pragma unroll
        for (int j = 1; j < 16; j++) {
          mx0 = fmaxf(mx0, fmaxf(s[4 * j], s[4 * j + 1]));
          mx1 = fmaxf(mx1, fmaxf(s[4 * j + 2], s[4 * j + 3]));
        }
        mx0 = fmaxf(mx0, __shfl_xor_sync(0xffffffffu, mx0, 1));
        mx1 = fmaxf(mx1, __shfl_xor_sync(0xffffffffu, mx1, 1));
        mx0 = fmaxf(mx0, __shfl_xor_sync(0xffffffffu, mx0, 2));
        mx1 = fmaxf(mx1, __shfl_xor_sync(0xffffffffu, mx1, 2));
        const float mn0 = fmaxf(m0, mx0), mn1 = fmaxf(m1, mx1);
        a0 = ex2((m0 - mn0) * sl2); a1 = ex2((m1 - mn1) * sl2);
        m0 = mn0; m1 = mn1;
        const float ms0 = mn0 * sl2, ms1 = mn1 * sl2;
        float rs0 = 0.f, rs1 = 0.f;
#pragma unroll
        for (int j = 0; j < 16; j++) {
          s[4 * j] = ex2(fmaf(s[4 * j], sl2, -ms0));
          s[4 * j + 1] = ex2(fmaf(s[4 * j + 1], sl2, -ms0));
          s[4 * j + 2] = ex2(fmaf(s[4 * j + 2], sl2, -ms1));
          s[4 * j + 3] = ex2(fmaf(s[4 * j + 3], sl2, -ms1));
          rs0 += s[4 * j] + s[4 * j + 1]; rs1 += s[4 * j + 2] + s[4 * j + 3];
        }
        l0 = l0 * a0 + rs0; l1 = l1 * a1 + rs1;
        reg_fence(s);
        TR(5);
      }
      if (qt > 0) {
        wgmma_wait<0>();
        reg_fence(o);
        release_v();
#pragma unroll
        for (int j = 0; j < 16; j++) {
          p[2 * j] = pack_bf16(s[4 * j], s[4 * j + 1]);
          p[2 * j + 1] = pack_bf16(s[4 * j + 2], s[4 * j + 3]);
        }
      }
      TI(4);
#pragma unroll
      for (int j = 0; j < 16; j++) {
        o[4 * j] *= a0; o[4 * j + 1] *= a0; o[4 * j + 2] *= a1; o[4 * j + 3] *= a1;
      }
      sched_sync();
      issue_pv();
      sched_arrive();
      l0 += __shfl_xor_sync(0xffffffffu, l0, 1); l0 += __shfl_xor_sync(0xffffffffu, l0, 2);
      l1 += __shfl_xor_sync(0xffffffffu, l1, 1); l1 += __shfl_xor_sync(0xffffffffu, l1, 2);
      const float inv0 = 1.f / l0, inv1 = 1.f / l1;
      wgmma_wait<0>();
      reg_fence(o);
      release_v();
      TI(5);
      if (tid == 0) tma_store_wait_read<0>();
      named_bar_sync(3 + cw, 128);
      {
        const int mi = lane >> 3;
        const int row = warp * 16 + (lane & 7) + (mi & 1) * 8;
        const uint32_t base = smem_u32(sm.ostage) + cw * 16384 + row * 128;
#pragma unroll
        for (int jj = 0; jj < 8; jj++) {
          uint32_t r0 = pack_bf16(o[8 * jj] * inv0, o[8 * jj + 1] * inv0);
          uint32_t r1 = pack_bf16(o[8 * jj + 2] * inv1, o[8 * jj + 3] * inv1);
          uint32_t r2 = pack_bf16(o[8 * jj + 4] * inv0, o[8 * jj + 5] * inv0);
          uint32_t r3 = pack_bf16(o[8 * jj + 6] * inv1, o[8 * jj + 7] * inv1);
          const int c = 2 * jj + (mi >> 1);
          const uint32_t addr = base + (c >> 3) * 8192 + (((c & 7) ^ (row & 7)) << 4);
          asm volatile("stmatrix.sync.aligned.m8n8.x4.shared.b16 [%0], {%1, %2, %3, %4};" ::"r"(addr), "r"(r0), "r"(r1), "r"(r2), "r"(r3) : "memory");
        }
      }
      fence_proxy_async_smem();
      named_bar_sync(3 + cw, 128);
      if (tid == 0) {
        tma_store_2d(&tmO, smem_u32(sm.ostage) + cw * 16384, head * HD, qt * 128 + cw * 64);
        tma_store_2d(&tmO, smem_u32(sm.ostage) + cw * 16384 + 8192, head * HD + 64, qt * 128 + cw * 64);
        tma_store_commit();
      }
      TI(6);
    }
    if (tid == 0) tma_store_wait<0>();
  }
}

__device__ __forceinline__ float bf16r(float x) { return __bfloat162float(__float2bfloat16_rn(x)); }

__global__ void __launch_bounds__(256) ln_kernel(const bf16* __restrict__ x, bf16* __restrict__ xn) {
  const int row = blockIdx.x * 8 + (threadIdx.x >> 5);
  const int lane = threadIdx.x & 31;
  const uint4* src = reinterpret_cast<const uint4*>(x + (size_t)row * DM) + lane * 2;
  uint4 v0 = src[0], v1 = src[1];
  float f[16];
  const uint32_t w[8] = {v0.x, v0.y, v0.z, v0.w, v1.x, v1.y, v1.z, v1.w};
#pragma unroll
  for (int i = 0; i < 8; i++) { f[2 * i] = __uint_as_float(w[i] << 16); f[2 * i + 1] = __uint_as_float(w[i] & 0xffff0000u); }
  float s = 0.f;
#pragma unroll
  for (int i = 0; i < 16; i++) s += f[i];
#pragma unroll
  for (int o = 16; o > 0; o >>= 1) s += __shfl_xor_sync(0xffffffffu, s, o);
  const float mean = s * (1.f / DM);
  float ss = 0.f;
#pragma unroll
  for (int i = 0; i < 16; i++) { float d = f[i] - mean; ss += d * d; }
#pragma unroll
  for (int o = 16; o > 0; o >>= 1) ss += __shfl_xor_sync(0xffffffffu, ss, o);
  const float mb = bf16r(mean);
  const float vb = bf16r(ss * (1.f / DM));
  const float den = bf16r(sqrtf(bf16r(vb + 1e-5f)));
  uint32_t o8[8];
#pragma unroll
  for (int i = 0; i < 8; i++) {
    float a = bf16r(f[2 * i] - mb) / den, b = bf16r(f[2 * i + 1] - mb) / den;
    o8[i] = pack_bf16(a, b);
  }
  uint4* dst = reinterpret_cast<uint4*>(xn + (size_t)row * DM) + lane * 2;
  dst[0] = make_uint4(o8[0], o8[1], o8[2], o8[3]);
  dst[1] = make_uint4(o8[4], o8[5], o8[6], o8[7]);
}

#define PT(ev) do {} while (0)
constexpr int PJ_ST = 12;
constexpr int PJ_NT = 110;
constexpr int PJ_UNITS = 8 * PJ_NT;
struct ProjSmem {
  uint8_t ring[PJ_ST][16384];
  uint8_t ostage[2][16384];
  uint64_t full[PJ_ST], empty[PJ_ST];
  uint64_t ord[2];
};
constexpr int PJ_SMEM_BYTES = sizeof(ProjSmem) + 1024;
struct ProjParams {
  CUtensorMap a[2];
  CUtensorMap b[4];
  CUtensorMap o[4];
};

__device__ __forceinline__ void proj_decode(int u, int& p, int& asrc, int& bm, int& ncol) {
  p = u / PJ_NT;
  int t = u - p * PJ_NT;
  if (t < 64) { asrc = 0; bm = t >> 5; ncol = (t & 31) * 128; }
  else if (t < 96) { asrc = 1; bm = 2; ncol = (t - 64) * 128; }
  else { asrc = 1; bm = 3; ncol = (t - 96) * 128; }
}

__global__ void __cluster_dims__(2, 1, 1) __launch_bounds__(384, 1)
proj_kernel(const __grid_constant__ ProjParams prm) {
  extern __shared__ uint8_t smem_raw[];
  ProjSmem& sm = *reinterpret_cast<ProjSmem*>((reinterpret_cast<uintptr_t>(smem_raw) + 1023) & ~uintptr_t(1023));
  const int wg = threadIdx.x >> 7;
  const uint32_t rank = cluster_ctarank();
  const int cl = blockIdx.x >> 1;
  const int ncl = gridDim.x >> 1;
  const int u0 = (int)(((long long)cl * PJ_UNITS) / ncl), u1 = (int)(((long long)(cl + 1) * PJ_UNITS) / ncl);

  if (threadIdx.x == 0) {
    for (int s = 0; s < PJ_ST; s++) { mbar_init(smem_u32(&sm.full[s]), 1); mbar_init(smem_u32(&sm.empty[s]), 16); }
    mbar_init(smem_u32(&sm.ord[0]), 4); mbar_init(smem_u32(&sm.ord[1]), 4);
    fence_barrier_init();
  }
  __syncthreads();
  cluster_sync_all();

  if (wg == 0) {
    reg_dealloc<40>();
    if (threadIdx.x == 0) {
      int st = 0; uint32_t ph = 0; int prev_key = -1;
      for (int u = u0; u < u1; u++) {
        int p, asrc, bm, ncol; proj_decode(u, p, asrc, bm, ncol);
        const int key = p * 2 + asrc;
        if (key != prev_key) {
          prev_key = key;
          for (int c = 0; c < 8; c++) {
            mbar_wait(smem_u32(&sm.empty[st]), ph ^ 1);
            mbar_expect_tx(smem_u32(&sm.full[st]), 16384);
            tma_load_2d(smem_u32(sm.ring[st]), &prm.a[asrc], smem_u32(&sm.full[st]), c * 64, (2 * p + rank) * 128);
            if (++st == PJ_ST) { st = 0; ph ^= 1; }
          }
        }
        for (int c = 0; c < 8; c++) {
          mbar_wait(smem_u32(&sm.empty[st]), ph ^ 1);
          mbar_expect_tx(smem_u32(&sm.full[st]), 16384);
          tma_load_2d_mc(smem_u32(sm.ring[st]) + rank * 8192, &prm.b[bm], smem_u32(&sm.full[st]), ncol + rank * 64, c * 64, (uint16_t)3);
          if (++st == PJ_ST) { st = 0; ph ^= 1; }
        }
      }
    }
  } else {
    reg_alloc<232>();
    const int cw = __shfl_sync(0xffffffffu, wg - 1, 0);
    const int tid = threadIdx.x & 127;
    const int warp = tid >> 5, lane = tid & 31;
    const uint32_t peer = rank ^ 1;
    int st = 0; uint32_t ph = 0; int prev_key = -1;
    uint32_t a[32][4];
    float acc[64];
    const uint64_t b_desc = make_desc(smem_u32(sm.ring[0]), 8192, 1024);
    auto release = [&](int s) {
      if (lane == 0) mbar_arrive(smem_u32(&sm.empty[s]));
      else if (lane == 1) mbar_arrive_cluster(smem_u32(&sm.empty[s]), peer);
    };
    for (int u = u0; u < u1; u++) {
      int p, asrc, bm, ncol; proj_decode(u, p, asrc, bm, ncol);
      const int key = p * 2 + asrc;
      PT(0);
      if (key != prev_key) {
        prev_key = key;
        const int mi = lane >> 3;
        const int row = cw * 64 + warp * 16 + (lane & 7) + (mi & 1) * 8;
#pragma unroll
        for (int c = 0; c < 8; c++) {
          mbar_wait(smem_u32(&sm.full[st]), ph);
          const uint32_t base = smem_u32(sm.ring[st]) + row * 128;
#pragma unroll
          for (int ks = 0; ks < 4; ks++) {
            const int ch = 2 * ks + (mi >> 1);
            const uint32_t addr = base + ((ch ^ (row & 7)) << 4);
            asm volatile("ldmatrix.sync.aligned.m8n8.x4.shared.b16 {%0, %1, %2, %3}, [%4];"
                         : "=r"(a[4 * c + ks][0]), "=r"(a[4 * c + ks][1]), "=r"(a[4 * c + ks][2]), "=r"(a[4 * c + ks][3]) : "r"(addr) : "memory");
          }
          __syncwarp();
          release(st);
          if (++st == PJ_ST) { st = 0; ph ^= 1; }
        }
      }
      int prev_st = 0;
      PT(1);
      mbar_wait(smem_u32(&sm.ord[cw]), ((u - u0) & 1) ^ (cw ^ 1));
      PT(2);
#pragma unroll
      for (int c = 0; c < 8; c++) {
        mbar_wait(smem_u32(&sm.full[st]), ph);
        const uint64_t bd = b_desc + (uint32_t)(st * (16384 >> 4));
        wgmma_fence();
#pragma unroll
        for (int ks = 0; ks < 4; ks++)
          wgmma_m64n128k16_rs<1>(acc, a[4 * c + ks][0], a[4 * c + ks][1], a[4 * c + ks][2], a[4 * c + ks][3], bd + (ks * 2048 >> 4), (c | ks) != 0);
        wgmma_commit();
        if (c > 0) { wgmma_wait<1>(); release(prev_st); }
        prev_st = st;
        if (++st == PJ_ST) { st = 0; ph ^= 1; }
      }
      PT(3);
      if (lane == 0) mbar_arrive(smem_u32(&sm.ord[cw ^ 1]));
      wgmma_wait<0>();
      reg_fence(acc);
      release(prev_st);
      PT(4);
      if (tid == 0) tma_store_wait_read<0>();
      named_bar_sync(1 + cw, 128);
      {
        const int mi = lane >> 3;
        const int row = warp * 16 + (lane & 7) + (mi & 1) * 8;
        const uint32_t base = smem_u32(sm.ostage[cw]) + row * 128;
        const bool relu = (bm == 3);
#pragma unroll
        for (int jj = 0; jj < 8; jj++) {
          float v[8];
#pragma unroll
          for (int e = 0; e < 8; e++) v[e] = relu ? fmaxf(acc[8 * jj + e], 0.f) : acc[8 * jj + e];
          const int c = 2 * jj + (mi >> 1);
          const uint32_t addr = base + (c >> 3) * 8192 + (((c & 7) ^ (row & 7)) << 4);
          asm volatile("stmatrix.sync.aligned.m8n8.x4.shared.b16 [%0], {%1, %2, %3, %4};" ::"r"(addr), "r"(pack_bf16(v[0], v[1])),
                       "r"(pack_bf16(v[2], v[3])), "r"(pack_bf16(v[4], v[5])), "r"(pack_bf16(v[6], v[7])) : "memory");
        }
      }
      fence_proxy_async_smem();
      named_bar_sync(1 + cw, 128);
      if (tid == 0) {
        const int orow = (2 * p + rank) * 128 + cw * 64;
        tma_store_2d(&prm.o[bm], smem_u32(sm.ostage[cw]), ncol, orow);
        tma_store_2d(&prm.o[bm], smem_u32(sm.ostage[cw]) + 8192, ncol + 64, orow);
        tma_store_commit();
      }
      PT(5);
    }
    if (tid == 0) tma_store_wait<0>();
  }
  __syncthreads();
  cluster_sync_all();
}

constexpr int FN_ST = 4;
constexpr int FN_KB_Y = DFF / 64;
constexpr int FN_KB = FN_KB_Y + HDT / 64;
constexpr int FN_KPS = FN_KB / 4;
struct FinSmem {
  uint8_t a[FN_ST][16384];
  uint8_t b[FN_ST][32768];
  uint64_t full[FN_ST], empty[FN_ST];
};
constexpr int FN_SMEM_BYTES = sizeof(FinSmem) + 1024;
struct FinParams {
  CUtensorMap a[2];
  CUtensorMap b[2];
};
__device__ __align__(16) float4 g_part[5][32][32][256];
__device__ unsigned int g_fin_cnt[32], g_fin_done[32];

__device__ __forceinline__ void red_add_v2(float* p, float a, float b) {
  asm volatile("red.global.add.v2.f32 [%0], {%1, %2};" ::"l"(p), "f"(a), "f"(b) : "memory");
}

__global__ void __cluster_dims__(2, 1, 1) __launch_bounds__(384, 1)
fin_kernel(const __grid_constant__ FinParams prm, const bf16* __restrict__ x, bf16* __restrict__ out) {
  extern __shared__ uint8_t smem_raw[];
  FinSmem& sm = *reinterpret_cast<FinSmem*>((reinterpret_cast<uintptr_t>(smem_raw) + 1023) & ~uintptr_t(1023));
  const int wg = threadIdx.x >> 7;
  const uint32_t rank = cluster_ctarank();
  const int cl = blockIdx.x >> 1;
  const int ksl = cl & 3, tp = cl >> 2;
  const int mblk = (tp >> 1) * 2 + rank, nhalf = tp & 1;
  const int kb0 = ksl * FN_KPS;

  if (threadIdx.x == 0) {
    for (int s = 0; s < FN_ST; s++) { mbar_init(smem_u32(&sm.full[s]), 1); mbar_init(smem_u32(&sm.empty[s]), 16); }
    fence_barrier_init();
  }
  __syncthreads();
  cluster_sync_all();

  if (wg == 0) {
    reg_dealloc<40>();
    if (threadIdx.x == 0) {
      int st = 0; uint32_t ph = 0;
      for (int i = 0; i < FN_KPS; i++) {
        const int kb = kb0 + i;
        const int src = kb < FN_KB_Y ? 0 : 1;
        const int kc = (src ? kb - FN_KB_Y : kb) * 64;
        mbar_wait(smem_u32(&sm.empty[st]), ph ^ 1);
        mbar_expect_tx(smem_u32(&sm.full[st]), 49152);
        tma_load_2d(smem_u32(sm.a[st]), &prm.a[src], smem_u32(&sm.full[st]), kc, mblk * 128);
#pragma unroll
        for (int j = 0; j < 2; j++) {
          const int box = rank * 2 + j;
          tma_load_2d_mc(smem_u32(sm.b[st]) + box * 8192, &prm.b[src], smem_u32(&sm.full[st]), nhalf * 256 + box * 64, kc, (uint16_t)3);
        }
        if (++st == FN_ST) { st = 0; ph ^= 1; }
      }
    }
  } else {
    reg_alloc<232>();
    const int cw = __shfl_sync(0xffffffffu, wg - 1, 0);
    const int tid = threadIdx.x & 127;
    const int warp = tid >> 5, lane = tid & 31;
    const uint32_t peer = rank ^ 1;
    int st = 0; uint32_t ph = 0;
    float acc[128];
    const uint64_t a_desc = make_desc(smem_u32(sm.a[0]) + cw * 8192, 16, 1024);
    const uint64_t b_desc = make_desc(smem_u32(sm.b[0]), 8192, 1024);
    const int row0 = mblk * 128 + cw * 64 + warp * 16 + (lane >> 2);
    const int col0 = nhalf * 256 + 2 * (lane & 3);
    const int tile = mblk * 2 + nhalf;
    auto flush = [&](int slot) {
      float4* dst = &g_part[slot][tile][0][threadIdx.x - 128];
#pragma unroll
      for (int j = 0; j < 32; j++) dst[j * 256] = make_float4(acc[4 * j], acc[4 * j + 1], acc[4 * j + 2], acc[4 * j + 3]);
    };
    int prev_st = -1;
    bool fresh = true;
    for (int i = 0; i < FN_KPS; i++) {
      const int kb = kb0 + i;
      if (kb == FN_KB_Y && i > 0) {
        wgmma_wait<0>();
        reg_fence(acc);
        if (lane == 0) mbar_arrive(smem_u32(&sm.empty[prev_st]));
        else if (lane == 1) mbar_arrive_cluster(smem_u32(&sm.empty[prev_st]), peer);
        prev_st = -1;
        flush(1);
        fresh = true;
      }
      mbar_wait(smem_u32(&sm.full[st]), ph);
      const uint64_t ad = a_desc + (uint32_t)(st * (16384 >> 4));
      const uint64_t bd = b_desc + (uint32_t)(st * (32768 >> 4));
      wgmma_fence();
#pragma unroll
      for (int ks = 0; ks < 4; ks++)
        wgmma_m64n256k16_ss<1>(acc, ad + (ks * 32 >> 4), bd + (ks * 2048 >> 4), !(fresh && ks == 0));
      wgmma_commit();
      fresh = false;
      if (prev_st >= 0) {
        wgmma_wait<1>();
        if (lane == 0) mbar_arrive(smem_u32(&sm.empty[prev_st]));
        else if (lane == 1) mbar_arrive_cluster(smem_u32(&sm.empty[prev_st]), peer);
      }
      prev_st = st;
      if (++st == FN_ST) { st = 0; ph ^= 1; }
    }
    wgmma_wait<0>();
    reg_fence(acc);
    if (lane == 0) mbar_arrive(smem_u32(&sm.empty[prev_st]));
    else if (lane == 1) mbar_arrive_cluster(smem_u32(&sm.empty[prev_st]), peer);
    flush(ksl == 0 ? 0 : ksl + 1);
    __threadfence();
    named_bar_sync(1, 256);
    if (threadIdx.x == 128) {
      atomicAdd(&g_fin_cnt[tile], 1u);
      unsigned int v;
      do { asm volatile("ld.acquire.gpu.global.u32 %0, [%1];" : "=r"(v) : "l"(&g_fin_cnt[tile]) : "memory"); } while (v < 4u);
    }
    named_bar_sync(1, 256);
    {
      const int t = threadIdx.x - 128;
      const int srct = 64 * ksl + (t & 63);
      const int jb = 8 * (t >> 6);
      float4 v[5][8];
#pragma unroll
      for (int sl = 0; sl < 5; sl++)
#pragma unroll
        for (int j = 0; j < 8; j++) v[sl][j] = __ldcg(&g_part[sl][tile][jb + j][srct]);
      const int l = srct & 31, wv = srct >> 5;
      const int r = mblk * 128 + (wv >> 2) * 64 + (wv & 3) * 16 + (l >> 2);
      uint32_t xr[8][2];
#pragma unroll
      for (int j = 0; j < 8; j++)
#pragma unroll
        for (int hh = 0; hh < 2; hh++)
          xr[j][hh] = *reinterpret_cast<const uint32_t*>(x + (size_t)(r + 8 * hh) * DM + nhalf * 256 + 8 * (jb + j) + 2 * (l & 3));
#pragma unroll
      for (int j = 0; j < 8; j++) {
        const int c = nhalf * 256 + 8 * (jb + j) + 2 * (l & 3);
        const float ys[4] = {v[0][j].x + v[1][j].x, v[0][j].y + v[1][j].y, v[0][j].z + v[1][j].z, v[0][j].w + v[1][j].w};
        const float ss[4] = {v[2][j].x + v[3][j].x + v[4][j].x, v[2][j].y + v[3][j].y + v[4][j].y,
                             v[2][j].z + v[3][j].z + v[4][j].z, v[2][j].w + v[3][j].w + v[4][j].w};
#pragma unroll
        for (int hh = 0; hh < 2; hh++) {
          const size_t off = (size_t)(r + 8 * hh) * DM + c;
          const uint32_t xv = xr[j][hh];
          float o[2];
#pragma unroll
          for (int e = 0; e < 2; e++) {
            const float y = bf16r(ys[2 * hh + e]);
            const float g = bf16r(y / (1.f + __expf(-y)));
            const float xe = e ? __uint_as_float(xv & 0xffff0000u) : __uint_as_float(xv << 16);
            o[e] = xe + bf16r(bf16r(ss[2 * hh + e]) * g);
          }
          *reinterpret_cast<uint32_t*>(out + off) = pack_bf16(o[0], o[1]);
        }
      }
    }
    named_bar_sync(1, 256);
    if (threadIdx.x == 128) {
      __threadfence();
      if (atomicAdd(&g_fin_done[tile], 1u) == 3u) { g_fin_cnt[tile] = 0u; g_fin_done[tile] = 0u; __threadfence(); }
    }
  }
  __syncthreads();
  cluster_sync_all();
}

typedef CUresult (*PFN_encodeTiled)(CUtensorMap*, CUtensorMapDataType, cuuint32_t, void*, const cuuint64_t*, const cuuint64_t*,
                                    const cuuint32_t*, const cuuint32_t*, CUtensorMapInterleave, CUtensorMapSwizzle,
                                    CUtensorMapL2promotion, CUtensorMapFloatOOBfill);

PFN_encodeTiled get_encode_fn() {
  static PFN_encodeTiled fn = nullptr;
  if (!fn) {
    void* p = nullptr;
    cudaDriverEntryPointQueryResult qr;
    cudaGetDriverEntryPoint("cuTensorMapEncodeTiled", &p, cudaEnableDefault, &qr);
    fn = (PFN_encodeTiled)p;
  }
  return fn;
}

CUtensorMap make_tmap(const void* ptr, uint64_t rows, uint64_t cols, uint32_t box_rows, uint32_t box_cols) {
  CUtensorMap tm;
  cuuint64_t gd[2] = {cols, rows};
  cuuint64_t gs[1] = {cols * 2};
  cuuint32_t box[2] = {box_cols, box_rows};
  cuuint32_t es[2] = {1, 1};
  get_encode_fn()(&tm, CU_TENSOR_MAP_DATA_TYPE_BFLOAT16, 2, const_cast<void*>(ptr), gd, gs, box, es, CU_TENSOR_MAP_INTERLEAVE_NONE,
                  CU_TENSOR_MAP_SWIZZLE_128B, CU_TENSOR_MAP_L2_PROMOTION_L2_256B, CU_TENSOR_MAP_FLOAT_OOB_FILL_NONE);
  return tm;
}

template <typename T> T* sym_addr(const T& sym) {
  void* p = nullptr;
  cudaGetSymbolAddress(&p, sym);
  return (T*)p;
}

}

extern "C" void kernel_launch(void* const* d_in, const int* in_sizes, int n_in, void* d_out, int out_size) {
  const bf16* x = (const bf16*)d_in[0];
  const bf16* ckv = (const bf16*)d_in[1];
  const bf16* wq = (const bf16*)d_in[2];
  const bf16* wuk = (const bf16*)d_in[3];
  const bf16* wuv = (const bf16*)d_in[4];
  const bf16* wo = (const bf16*)d_in[5];
  const bf16* w1 = (const bf16*)d_in[7];
  const bf16* w2 = (const bf16*)d_in[8];
  bf16* xn = sym_addr(g_xn[0]) ; bf16* q = sym_addr(g_q[0]); bf16* k = sym_addr(g_k[0]); bf16* v = sym_addr(g_v[0]);
  bf16* h = sym_addr(g_h[0]); bf16* ctx = sym_addr(g_ctx[0]);

  ln_kernel<<<SEQ / 8, 256>>>(x, xn);

  ProjParams pp;
  pp.a[0] = make_tmap(ckv, SEQ, DM, 128, 64);
  pp.a[1] = make_tmap(xn, SEQ, DM, 128, 64);
  pp.b[0] = make_tmap(wuk, DM, HDT, 64, 64);
  pp.b[1] = make_tmap(wuv, DM, HDT, 64, 64);
  pp.b[2] = make_tmap(wq, DM, HDT, 64, 64);
  pp.b[3] = make_tmap(w1, DM, DFF, 64, 64);
  pp.o[0] = make_tmap(k, SEQ, HDT, 64, 64);
  pp.o[1] = make_tmap(v, SEQ, HDT, 64, 64);
  pp.o[2] = make_tmap(q, SEQ, HDT, 64, 64);
  pp.o[3] = make_tmap(h, SEQ, DFF, 64, 64);
  cudaFuncSetAttribute(proj_kernel, cudaFuncAttributeMaxDynamicSharedMemorySize, PJ_SMEM_BYTES);
  proj_kernel<<<132, 384, PJ_SMEM_BYTES>>>(pp);

  CUtensorMap tmQ = make_tmap(q, SEQ, HDT, 128, 64);
  CUtensorMap tmK = make_tmap(k, SEQ, HDT, 128, 64);
  CUtensorMap tmV = make_tmap(v, SEQ, HDT, 128, 64);
  CUtensorMap tmO = make_tmap(ctx, SEQ, HDT, 64, 64);
  cudaFuncSetAttribute(attn_kernel, cudaFuncAttributeMaxDynamicSharedMemorySize, ATT_SMEM_BYTES);
  attn_kernel<<<128, 384, ATT_SMEM_BYTES>>>(tmQ, tmK, tmV, tmO);

  FinParams fp;
  fp.a[0] = make_tmap(h, SEQ, DFF, 128, 64);
  fp.a[1] = make_tmap(ctx, SEQ, HDT, 128, 64);
  fp.b[0] = make_tmap(w2, DFF, DM, 64, 64);
  fp.b[1] = make_tmap(wo, HDT, DM, 64, 64);
  cudaFuncSetAttribute(fin_kernel, cudaFuncAttributeMaxDynamicSharedMemorySize, FN_SMEM_BYTES);
  fin_kernel<<<128, 384, FN_SMEM_BYTES>>>(fp, x, (bf16*)d_out);
}
```

```cpp
#include <cuda_runtime.h>
#include <cuda_bf16.h>
#include <cuda.h>
#include <stdint.h>

typedef __nv_bfloat16 bf16;

namespace {

constexpr int SEQ = 2048;
constexpr int DM  = 512;
constexpr int NH  = 32;
constexpr int HD  = 128;
constexpr int HDT = NH * HD;
constexpr int DFF = 1792;

__device__ __align__(1024) bf16 g_xn[SEQ * DM];
__device__ __align__(1024) bf16 g_q[SEQ * HDT];
__device__ __align__(1024) bf16 g_k[SEQ * HDT];
__device__ __align__(1024) bf16 g_v[SEQ * HDT];
__device__ __align__(1024) bf16 g_h[SEQ * DFF];
__device__ __align__(1024) bf16 g_ctx[SEQ * HDT];

__device__ __forceinline__ uint32_t smem_u32(const void* p) { return (uint32_t)__cvta_generic_to_shared(p); }

__device__ __forceinline__ void mbar_init(uint32_t bar, uint32_t cnt) {
  asm volatile("mbarrier.init.shared::cta.b64 [%0], %1;" ::"r"(bar), "r"(cnt));
}
__device__ __forceinline__ void mbar_expect_tx(uint32_t bar, uint32_t bytes) {
  asm volatile("mbarrier.arrive.expect_tx.shared::cta.b64 _, [%0], %1;" ::"r"(bar), "r"(bytes) : "memory");
}
__device__ __forceinline__ void mbar_arrive(uint32_t bar) {
  asm volatile("mbarrier.arrive.shared::cta.b64 _, [%0];" ::"r"(bar) : "memory");
}
__device__ __forceinline__ void mbar_arrive_cluster(uint32_t bar, uint32_t cta) {
  asm volatile("{\n.reg .b32 ra;\nmapa.shared::cluster.u32 ra, %0, %1;\nmbarrier.arrive.shared::cluster.b64 _, [ra];\n}\n" ::"r"(bar), "r"(cta) : "memory");
}
__device__ __forceinline__ bool mbar_try_wait(uint32_t bar, uint32_t parity) {
  uint32_t ok;
  asm volatile("{\n.reg .pred p;\nmbarrier.try_wait.parity.shared::cta.b64 p, [%1], %2;\nselp.u32 %0, 1, 0, p;\n}\n" : "=r"(ok) : "r"(bar), "r"(parity) : "memory");
  return ok != 0;
}
__device__ __forceinline__ void mbar_wait(uint32_t bar, uint32_t parity) {
  while (!mbar_try_wait(bar, parity)) {}
}
__device__ __forceinline__ void fence_barrier_init() { asm volatile("fence.mbarrier_init.release.cluster;" ::: "memory"); }
__device__ __forceinline__ void fence_proxy_async() { asm volatile("fence.proxy.async;" ::: "memory"); }
__device__ __forceinline__ void fence_proxy_async_smem() { asm volatile("fence.proxy.async.shared::cta;" ::: "memory"); }

__device__ __forceinline__ void tma_load_2d(uint32_t dst, const CUtensorMap* tm, uint32_t bar, int c0, int c1) {
  asm volatile("cp.async.bulk.tensor.2d.shared::cluster.global.mbarrier::complete_tx::bytes [%0], [%1, {%3, %4}], [%2];"
               ::"r"(dst), "l"(tm), "r"(bar), "r"(c0), "r"(c1) : "memory");
}
__device__ __forceinline__ void tma_load_2d_mc(uint32_t dst, const CUtensorMap* tm, uint32_t bar, int c0, int c1, uint16_t mask) {
  asm volatile("cp.async.bulk.tensor.2d.shared::cluster.global.mbarrier::complete_tx::bytes.multicast::cluster [%0], [%1, {%3, %4}], [%2], %5;"
               ::"r"(dst), "l"(tm), "r"(bar), "r"(c0), "r"(c1), "h"(mask) : "memory");
}
__device__ __forceinline__ void tma_store_2d(const CUtensorMap* tm, uint32_t src, int c0, int c1) {
  asm volatile("cp.async.bulk.tensor.2d.global.shared::cta.bulk_group [%0, {%2, %3}], [%1];"
               ::"l"(tm), "r"(src), "r"(c0), "r"(c1) : "memory");
}
__device__ __forceinline__ void tma_store_commit() { asm volatile("cp.async.bulk.commit_group;" ::: "memory"); }
template <int N> __device__ __forceinline__ void tma_store_wait_read() { asm volatile("cp.async.bulk.wait_group.read %0;" ::"n"(N) : "memory"); }
template <int N> __device__ __forceinline__ void tma_store_wait() { asm volatile("cp.async.bulk.wait_group %0;" ::"n"(N) : "memory"); }
__device__ __forceinline__ void prefetch_tmap(const CUtensorMap* tm) { asm volatile("prefetch.tensormap [%0];" ::"l"(tm) : "memory"); }

__device__ __forceinline__ void named_bar_sync(int id, int nthreads) { asm volatile("bar.sync %0, %1;" ::"r"(id), "r"(nthreads) : "memory"); }
__device__ __forceinline__ void named_bar_arrive(int id, int nthreads) { asm volatile("bar.arrive %0, %1;" ::"r"(id), "r"(nthreads) : "memory"); }

__device__ __forceinline__ uint32_t cluster_ctarank() { uint32_t r; asm volatile("mov.u32 %0, %%cluster_ctarank;" : "=r"(r)); return r; }
__device__ __forceinline__ void cluster_sync_all() { asm volatile("barrier.cluster.arrive.release.aligned;\nbarrier.cluster.wait.acquire.aligned;" ::: "memory"); }

template <int R> __device__ __forceinline__ void reg_alloc() { asm volatile("setmaxnreg.inc.sync.aligned.u32 %0;" ::"n"(R)); }
template <int R> __device__ __forceinline__ void reg_dealloc() { asm volatile("setmaxnreg.dec.sync.aligned.u32 %0;" ::"n"(R)); }

__device__ __forceinline__ void pdl_wait() { asm volatile("griddepcontrol.wait;" ::: "memory"); }
__device__ __forceinline__ void pdl_launch() { asm volatile("griddepcontrol.launch_dependents;" ::: "memory"); }
__device__ __forceinline__ void wgmma_fence() { asm volatile("wgmma.fence.sync.aligned;" ::: "memory"); }
__device__ __forceinline__ void wgmma_commit() { asm volatile("wgmma.commit_group.sync.aligned;" ::: "memory"); }
template <int N> __device__ __forceinline__ void wgmma_wait() { asm volatile("wgmma.wait_group.sync.aligned %0;" ::"n"(N) : "memory"); }

__device__ __forceinline__ uint64_t make_desc(uint32_t saddr, uint32_t lbo, uint32_t sbo) {
  uint64_t d = 0;
  d |= (uint64_t)((saddr & 0x3FFFF) >> 4);
  d |= (uint64_t)((lbo & 0x3FFFF) >> 4) << 16;
  d |= (uint64_t)((sbo & 0x3FFFF) >> 4) << 32;
  d |= (uint64_t)1 << 62;
  return d;
}

__device__ __forceinline__ uint32_t pack_bf16(float lo, float hi) {
  uint32_t r;
  asm("cvt.rn.bf16x2.f32 %0, %1, %2;" : "=r"(r) : "f"(hi), "f"(lo));
  return r;
}
__device__ __forceinline__ float ex2(float x) { float y; asm("ex2.approx.ftz.f32 %0, %1;" : "=f"(y) : "f"(x)); return y; }

template<int TB> __device__ __forceinline__ void wgmma_m64n128k16_ss(float (&d)[64], uint64_t da, uint64_t db, int scale_d) {
  asm volatile("{\n.reg .pred p;\nsetp.ne.b32 p, %66, 0;\nwgmma.mma_async.sync.aligned.m64n128k16.f32.bf16.bf16 {%0, %1, %2, %3, %4, %5, %6, %7, %8, %9, %10, %11, %12, %13, %14, %15, %16, %17, %18, %19, %20, %21, %22, %23, %24, %25, %26, %27, %28, %29, %30, %31, %32, %33, %34, %35, %36, %37, %38, %39, %40, %41, %42, %43, %44, %45, %46, %47, %48, %49, %50, %51, %52, %53, %54, %55, %56, %57, %58, %59, %60, %61, %62, %63}, %64, %65, p, 1, 1, 0, %67;\n}\n"
    : "+f"(d[0]), "+f"(d[1]), "+f"(d[2]), "+f"(d[3]), "+f"(d[4]), "+f"(d[5]), "+f"(d[6]), "+f"(d[7]), "+f"(d[8]), "+f"(d[9]), "+f"(d[10]), "+f"(d[11]), "+f"(d[12]), "+f"(d[13]), "+f"(d[14]), "+f"(d[15]), "+f"(d[16]), "+f"(d[17]), "+f"(d[18]), "+f"(d[19]), "+f"(d[20]), "+f"(d[21]), "+f"(d[22]), "+f"(d[23]), "+f"(d[24]), "+f"(d[25]), "+f"(d[26]), "+f"(d[27]), "+f"(d[28]), "+f"(d[29]), "+f"(d[30]), "+f"(d[31]), "+f"(d[32]), "+f"(d[33]), "+f"(d[34]), "+f"(d[35]), "+f"(d[36]), "+f"(d[37]), "+f"(d[38]), "+f"(d[39]), "+f"(d[40]), "+f"(d[41]), "+f"(d[42]), "+f"(d[43]), "+f"(d[44]), "+f"(d[45]), "+f"(d[46]), "+f"(d[47]), "+f"(d[48]), "+f"(d[49]), "+f"(d[50]), "+f"(d[51]), "+f"(d[52]), "+f"(d[53]), "+f"(d[54]), "+f"(d[55]), "+f"(d[56]), "+f"(d[57]), "+f"(d[58]), "+f"(d[59]), "+f"(d[60]), "+f"(d[61]), "+f"(d[62]), "+f"(d[63])
    : "l"(da), "l"(db), "r"(scale_d), "n"(TB));
}

template<int TB> __device__ __forceinline__ void wgmma_m64n128k16_rs(float (&d)[64], uint32_t a0, uint32_t a1, uint32_t a2, uint32_t a3, uint64_t db, int scale_d) {
  asm volatile("{\n.reg .pred p;\nsetp.ne.b32 p, %69, 0;\nwgmma.mma_async.sync.aligned.m64n128k16.f32.bf16.bf16 {%0, %1, %2, %3, %4, %5, %6, %7, %8, %9, %10, %11, %12, %13, %14, %15, %16, %17, %18, %19, %20, %21, %22, %23, %24, %25, %26, %27, %28, %29, %30, %31, %32, %33, %34, %35, %36, %37, %38, %39, %40, %41, %42, %43, %44, %45, %46, %47, %48, %49, %50, %51, %52, %53, %54, %55, %56, %57, %58, %59, %60, %61, %62, %63}, {%64, %65, %66, %67}, %68, p, 1, 1, %70;\n}\n"
    : "+f"(d[0]), "+f"(d[1]), "+f"(d[2]), "+f"(d[3]), "+f"(d[4]), "+f"(d[5]), "+f"(d[6]), "+f"(d[7]), "+f"(d[8]), "+f"(d[9]), "+f"(d[10]), "+f"(d[11]), "+f"(d[12]), "+f"(d[13]), "+f"(d[14]), "+f"(d[15]), "+f"(d[16]), "+f"(d[17]), "+f"(d[18]), "+f"(d[19]), "+f"(d[20]), "+f"(d[21]), "+f"(d[22]), "+f"(d[23]), "+f"(d[24]), "+f"(d[25]), "+f"(d[26]), "+f"(d[27]), "+f"(d[28]), "+f"(d[29]), "+f"(d[30]), "+f"(d[31]), "+f"(d[32]), "+f"(d[33]), "+f"(d[34]), "+f"(d[35]), "+f"(d[36]), "+f"(d[37]), "+f"(d[38]), "+f"(d[39]), "+f"(d[40]), "+f"(d[41]), "+f"(d[42]), "+f"(d[43]), "+f"(d[44]), "+f"(d[45]), "+f"(d[46]), "+f"(d[47]), "+f"(d[48]), "+f"(d[49]), "+f"(d[50]), "+f"(d[51]), "+f"(d[52]), "+f"(d[53]), "+f"(d[54]), "+f"(d[55]), "+f"(d[56]), "+f"(d[57]), "+f"(d[58]), "+f"(d[59]), "+f"(d[60]), "+f"(d[61]), "+f"(d[62]), "+f"(d[63])
    : "r"(a0), "r"(a1), "r"(a2), "r"(a3), "l"(db), "r"(scale_d), "n"(TB));
}

template<int TB> __device__ __forceinline__ void wgmma_m64n256k16_ss(float (&d)[128], uint64_t da, uint64_t db, int scale_d) {
  asm volatile("{\n.reg .pred p;\nsetp.ne.b32 p, %130, 0;\nwgmma.mma_async.sync.aligned.m64n256k16.f32.bf16.bf16 {%0, %1, %2, %3, %4, %5, %6, %7, %8, %9, %10, %11, %12, %13, %14, %15, %16, %17, %18, %19, %20, %21, %22, %23, %24, %25, %26, %27, %28, %29, %30, %31, %32, %33, %34, %35, %36, %37, %38, %39, %40, %41, %42, %43, %44, %45, %46, %47, %48, %49, %50, %51, %52, %53, %54, %55, %56, %57, %58, %59, %60, %61, %62, %63, %64, %65, %66, %67, %68, %69, %70, %71, %72, %73, %74, %75, %76, %77, %78, %79, %80, %81, %82, %83, %84, %85, %86, %87, %88, %89, %90, %91, %92, %93, %94, %95, %96, %97, %98, %99, %100, %101, %102, %103, %104, %105, %106, %107, %108, %109, %110, %111, %112, %113, %114, %115, %116, %117, %118, %119, %120, %121, %122, %123, %124, %125, %126, %127}, %128, %129, p, 1, 1, 0, %131;\n}\n"
    : "+f"(d[0]), "+f"(d[1]), "+f"(d[2]), "+f"(d[3]), "+f"(d[4]), "+f"(d[5]), "+f"(d[6]), "+f"(d[7]), "+f"(d[8]), "+f"(d[9]), "+f"(d[10]), "+f"(d[11]), "+f"(d[12]), "+f"(d[13]), "+f"(d[14]), "+f"(d[15]), "+f"(d[16]), "+f"(d[17]), "+f"(d[18]), "+f"(d[19]), "+f"(d[20]), "+f"(d[21]), "+f"(d[22]), "+f"(d[23]), "+f"(d[24]), "+f"(d[25]), "+f"(d[26]), "+f"(d[27]), "+f"(d[28]), "+f"(d[29]), "+f"(d[30]), "+f"(d[31]), "+f"(d[32]), "+f"(d[33]), "+f"(d[34]), "+f"(d[35]), "+f"(d[36]), "+f"(d[37]), "+f"(d[38]), "+f"(d[39]), "+f"(d[40]), "+f"(d[41]), "+f"(d[42]), "+f"(d[43]), "+f"(d[44]), "+f"(d[45]), "+f"(d[46]), "+f"(d[47]), "+f"(d[48]), "+f"(d[49]), "+f"(d[50]), "+f"(d[51]), "+f"(d[52]), "+f"(d[53]), "+f"(d[54]), "+f"(d[55]), "+f"(d[56]), "+f"(d[57]), "+f"(d[58]), "+f"(d[59]), "+f"(d[60]), "+f"(d[61]), "+f"(d[62]), "+f"(d[63]), "+f"(d[64]), "+f"(d[65]), "+f"(d[66]), "+f"(d[67]), "+f"(d[68]), "+f"(d[69]), "+f"(d[70]), "+f"(d[71]), "+f"(d[72]), "+f"(d[73]), "+f"(d[74]), "+f"(d[75]), "+f"(d[76]), "+f"(d[77]), "+f"(d[78]), "+f"(d[79]), "+f"(d[80]), "+f"(d[81]), "+f"(d[82]), "+f"(d[83]), "+f"(d[84]), "+f"(d[85]), "+f"(d[86]), "+f"(d[87]), "+f"(d[88]), "+f"(d[89]), "+f"(d[90]), "+f"(d[91]), "+f"(d[92]), "+f"(d[93]), "+f"(d[94]), "+f"(d[95]), "+f"(d[96]), "+f"(d[97]), "+f"(d[98]), "+f"(d[99]), "+f"(d[100]), "+f"(d[101]), "+f"(d[102]), "+f"(d[103]), "+f"(d[104]), "+f"(d[105]), "+f"(d[106]), "+f"(d[107]), "+f"(d[108]), "+f"(d[109]), "+f"(d[110]), "+f"(d[111]), "+f"(d[112]), "+f"(d[113]), "+f"(d[114]), "+f"(d[115]), "+f"(d[116]), "+f"(d[117]), "+f"(d[118]), "+f"(d[119]), "+f"(d[120]), "+f"(d[121]), "+f"(d[122]), "+f"(d[123]), "+f"(d[124]), "+f"(d[125]), "+f"(d[126]), "+f"(d[127])
    : "l"(da), "l"(db), "r"(scale_d), "n"(TB));
}

template<int TB> __device__ __forceinline__ void wgmma_m64n64k16_ss(float (&d)[32], uint64_t da, uint64_t db, int scale_d) {
  asm volatile("{\n.reg .pred p;\nsetp.ne.b32 p, %34, 0;\nwgmma.mma_async.sync.aligned.m64n64k16.f32.bf16.bf16 {%0, %1, %2, %3, %4, %5, %6, %7, %8, %9, %10, %11, %12, %13, %14, %15, %16, %17, %18, %19, %20, %21, %22, %23, %24, %25, %26, %27, %28, %29, %30, %31}, %32, %33, p, 1, 1, 0, %35;\n}\n"
    : "+f"(d[0]), "+f"(d[1]), "+f"(d[2]), "+f"(d[3]), "+f"(d[4]), "+f"(d[5]), "+f"(d[6]), "+f"(d[7]), "+f"(d[8]), "+f"(d[9]), "+f"(d[10]), "+f"(d[11]), "+f"(d[12]), "+f"(d[13]), "+f"(d[14]), "+f"(d[15]), "+f"(d[16]), "+f"(d[17]), "+f"(d[18]), "+f"(d[19]), "+f"(d[20]), "+f"(d[21]), "+f"(d[22]), "+f"(d[23]), "+f"(d[24]), "+f"(d[25]), "+f"(d[26]), "+f"(d[27]), "+f"(d[28]), "+f"(d[29]), "+f"(d[30]), "+f"(d[31])
    : "l"(da), "l"(db), "r"(scale_d), "n"(TB));
}

template<int TB> __device__ __forceinline__ void wgmma_m64n64k16_rs(float (&d)[32], uint32_t a0, uint32_t a1, uint32_t a2, uint32_t a3, uint64_t db, int scale_d) {
  asm volatile("{\n.reg .pred p;\nsetp.ne.b32 p, %37, 0;\nwgmma.mma_async.sync.aligned.m64n64k16.f32.bf16.bf16 {%0, %1, %2, %3, %4, %5, %6, %7, %8, %9, %10, %11, %12, %13, %14, %15, %16, %17, %18, %19, %20, %21, %22, %23, %24, %25, %26, %27, %28, %29, %30, %31}, {%32, %33, %34, %35}, %36, p, 1, 1, %38;\n}\n"
    : "+f"(d[0]), "+f"(d[1]), "+f"(d[2]), "+f"(d[3]), "+f"(d[4]), "+f"(d[5]), "+f"(d[6]), "+f"(d[7]), "+f"(d[8]), "+f"(d[9]), "+f"(d[10]), "+f"(d[11]), "+f"(d[12]), "+f"(d[13]), "+f"(d[14]), "+f"(d[15]), "+f"(d[16]), "+f"(d[17]), "+f"(d[18]), "+f"(d[19]), "+f"(d[20]), "+f"(d[21]), "+f"(d[22]), "+f"(d[23]), "+f"(d[24]), "+f"(d[25]), "+f"(d[26]), "+f"(d[27]), "+f"(d[28]), "+f"(d[29]), "+f"(d[30]), "+f"(d[31])
    : "r"(a0), "r"(a1), "r"(a2), "r"(a3), "l"(db), "r"(scale_d), "n"(TB));
}

__device__ __forceinline__ void reg_fence(float (&d)[32]) {
  asm volatile("" : "+f"(d[0]), "+f"(d[1]), "+f"(d[2]), "+f"(d[3]), "+f"(d[4]), "+f"(d[5]), "+f"(d[6]), "+f"(d[7]), "+f"(d[8]), "+f"(d[9]), "+f"(d[10]), "+f"(d[11]), "+f"(d[12]), "+f"(d[13]), "+f"(d[14]), "+f"(d[15]), "+f"(d[16]), "+f"(d[17]), "+f"(d[18]), "+f"(d[19]), "+f"(d[20]), "+f"(d[21]), "+f"(d[22]), "+f"(d[23]), "+f"(d[24]), "+f"(d[25]), "+f"(d[26]), "+f"(d[27]), "+f"(d[28]), "+f"(d[29]), "+f"(d[30]), "+f"(d[31]) :: "memory");
}

__device__ __forceinline__ void reg_fence(float (&d)[64]) {
  asm volatile("" : "+f"(d[0]), "+f"(d[1]), "+f"(d[2]), "+f"(d[3]), "+f"(d[4]), "+f"(d[5]), "+f"(d[6]), "+f"(d[7]), "+f"(d[8]), "+f"(d[9]), "+f"(d[10]), "+f"(d[11]), "+f"(d[12]), "+f"(d[13]), "+f"(d[14]), "+f"(d[15]), "+f"(d[16]), "+f"(d[17]), "+f"(d[18]), "+f"(d[19]), "+f"(d[20]), "+f"(d[21]), "+f"(d[22]), "+f"(d[23]), "+f"(d[24]), "+f"(d[25]), "+f"(d[26]), "+f"(d[27]), "+f"(d[28]), "+f"(d[29]), "+f"(d[30]), "+f"(d[31]), "+f"(d[32]), "+f"(d[33]), "+f"(d[34]), "+f"(d[35]), "+f"(d[36]), "+f"(d[37]), "+f"(d[38]), "+f"(d[39]), "+f"(d[40]), "+f"(d[41]), "+f"(d[42]), "+f"(d[43]), "+f"(d[44]), "+f"(d[45]), "+f"(d[46]), "+f"(d[47]), "+f"(d[48]), "+f"(d[49]), "+f"(d[50]), "+f"(d[51]), "+f"(d[52]), "+f"(d[53]), "+f"(d[54]), "+f"(d[55]), "+f"(d[56]), "+f"(d[57]), "+f"(d[58]), "+f"(d[59]), "+f"(d[60]), "+f"(d[61]), "+f"(d[62]), "+f"(d[63]) :: "memory");
}

__device__ __forceinline__ void reg_fence(float (&d)[128]) {
  asm volatile("" : "+f"(d[0]), "+f"(d[1]), "+f"(d[2]), "+f"(d[3]), "+f"(d[4]), "+f"(d[5]), "+f"(d[6]), "+f"(d[7]), "+f"(d[8]), "+f"(d[9]), "+f"(d[10]), "+f"(d[11]), "+f"(d[12]), "+f"(d[13]), "+f"(d[14]), "+f"(d[15]), "+f"(d[16]), "+f"(d[17]), "+f"(d[18]), "+f"(d[19]), "+f"(d[20]), "+f"(d[21]), "+f"(d[22]), "+f"(d[23]), "+f"(d[24]), "+f"(d[25]), "+f"(d[26]), "+f"(d[27]), "+f"(d[28]), "+f"(d[29]), "+f"(d[30]), "+f"(d[31]), "+f"(d[32]), "+f"(d[33]), "+f"(d[34]), "+f"(d[35]), "+f"(d[36]), "+f"(d[37]), "+f"(d[38]), "+f"(d[39]), "+f"(d[40]), "+f"(d[41]), "+f"(d[42]), "+f"(d[43]), "+f"(d[44]), "+f"(d[45]), "+f"(d[46]), "+f"(d[47]), "+f"(d[48]), "+f"(d[49]), "+f"(d[50]), "+f"(d[51]), "+f"(d[52]), "+f"(d[53]), "+f"(d[54]), "+f"(d[55]), "+f"(d[56]), "+f"(d[57]), "+f"(d[58]), "+f"(d[59]), "+f"(d[60]), "+f"(d[61]), "+f"(d[62]), "+f"(d[63]), "+f"(d[64]), "+f"(d[65]), "+f"(d[66]), "+f"(d[67]), "+f"(d[68]), "+f"(d[69]), "+f"(d[70]), "+f"(d[71]), "+f"(d[72]), "+f"(d[73]), "+f"(d[74]), "+f"(d[75]), "+f"(d[76]), "+f"(d[77]), "+f"(d[78]), "+f"(d[79]), "+f"(d[80]), "+f"(d[81]), "+f"(d[82]), "+f"(d[83]), "+f"(d[84]), "+f"(d[85]), "+f"(d[86]), "+f"(d[87]), "+f"(d[88]), "+f"(d[89]), "+f"(d[90]), "+f"(d[91]), "+f"(d[92]), "+f"(d[93]), "+f"(d[94]), "+f"(d[95]), "+f"(d[96]), "+f"(d[97]), "+f"(d[98]), "+f"(d[99]), "+f"(d[100]), "+f"(d[101]), "+f"(d[102]), "+f"(d[103]), "+f"(d[104]), "+f"(d[105]), "+f"(d[106]), "+f"(d[107]), "+f"(d[108]), "+f"(d[109]), "+f"(d[110]), "+f"(d[111]), "+f"(d[112]), "+f"(d[113]), "+f"(d[114]), "+f"(d[115]), "+f"(d[116]), "+f"(d[117]), "+f"(d[118]), "+f"(d[119]), "+f"(d[120]), "+f"(d[121]), "+f"(d[122]), "+f"(d[123]), "+f"(d[124]), "+f"(d[125]), "+f"(d[126]), "+f"(d[127]) :: "memory");
}

#define ATT_PINGPONG 1
#define TR(ev) do {} while (0)
#define TI(ev) do {} while (0)
constexpr int ATT_K_ST = 3, ATT_V_ST = 2;
constexpr int ATT_TILE_BYTES = 128 * 128 * 2;
struct AttnSmem {
  uint8_t q[ATT_TILE_BYTES];
  uint8_t k[ATT_K_ST][ATT_TILE_BYTES];
  uint8_t v[ATT_V_ST][ATT_TILE_BYTES];
  uint8_t ostage[ATT_TILE_BYTES];
  uint64_t q_full, q_empty;
  uint64_t ord[2];
  uint64_t k_full[ATT_K_ST], k_empty[ATT_K_ST], v_full[ATT_V_ST], v_empty[ATT_V_ST];
};
constexpr int ATT_SMEM_BYTES = sizeof(AttnSmem) + 1024;
constexpr int ATT_ITEMS_PER_CTA = 4;

__device__ __forceinline__ void attn_item(int cta, int it, int& head, int& qt) {
  head = 8 * it + (cta >> 4);
  int r = cta & 15;
  qt = (it & 1) ? (15 - r) : r;
}

__global__ void __launch_bounds__(384, 1)
attn_kernel(const __grid_constant__ CUtensorMap tmQ, const __grid_constant__ CUtensorMap tmK,
            const __grid_constant__ CUtensorMap tmV, const __grid_constant__ CUtensorMap tmO) {
  extern __shared__ uint8_t smem_raw[];
  AttnSmem& sm = *reinterpret_cast<AttnSmem*>((reinterpret_cast<uintptr_t>(smem_raw) + 1023) & ~uintptr_t(1023));
  const int wg = threadIdx.x >> 7;
  const int cta = blockIdx.x;

  if (threadIdx.x == 0) {
    mbar_init(smem_u32(&sm.q_full), 1);
    mbar_init(smem_u32(&sm.q_empty), 8);
    mbar_init(smem_u32(&sm.ord[0]), 4); mbar_init(smem_u32(&sm.ord[1]), 4);
    for (int s = 0; s < ATT_K_ST; s++) {
      mbar_init(smem_u32(&sm.k_full[s]), 1);
      mbar_init(smem_u32(&sm.k_empty[s]), 8);
    }
    for (int s = 0; s < ATT_V_ST; s++) {
      mbar_init(smem_u32(&sm.v_full[s]), 1);
      mbar_init(smem_u32(&sm.v_empty[s]), 8);
    }
    fence_barrier_init();
  }
  __syncthreads();
  pdl_launch();
  pdl_wait();

  if (wg == 0) {
    reg_dealloc<40>();
    if (threadIdx.x == 0) {
      int kst = 0, vst = 0; uint32_t kph = 0, vph = 0;
      for (int it = 0; it < ATT_ITEMS_PER_CTA; it++) {
        int head, qt; attn_item(cta, it, head, qt);
        mbar_wait(smem_u32(&sm.q_empty), (it & 1) ^ 1);
        mbar_expect_tx(smem_u32(&sm.q_full), ATT_TILE_BYTES);
        tma_load_2d(smem_u32(sm.q), &tmQ, smem_u32(&sm.q_full), head * HD, qt * 128);
        tma_load_2d(smem_u32(sm.q) + 16384, &tmQ, smem_u32(&sm.q_full), head * HD + 64, qt * 128);
        for (int n = qt; n >= 0; --n) {
          mbar_wait(smem_u32(&sm.k_empty[kst]), kph ^ 1);
          mbar_expect_tx(smem_u32(&sm.k_full[kst]), ATT_TILE_BYTES);
          tma_load_2d(smem_u32(sm.k[kst]), &tmK, smem_u32(&sm.k_full[kst]), head * HD, n * 128);
          tma_load_2d(smem_u32(sm.k[kst]) + 16384, &tmK, smem_u32(&sm.k_full[kst]), head * HD + 64, n * 128);
          if (++kst == ATT_K_ST) { kst = 0; kph ^= 1; }
          mbar_wait(smem_u32(&sm.v_empty[vst]), vph ^ 1);
          mbar_expect_tx(smem_u32(&sm.v_full[vst]), ATT_TILE_BYTES);
          tma_load_2d(smem_u32(sm.v[vst]), &tmV, smem_u32(&sm.v_full[vst]), head * HD, n * 128);
          tma_load_2d(smem_u32(sm.v[vst]) + 16384, &tmV, smem_u32(&sm.v_full[vst]), head * HD + 64, n * 128);
          if (++vst == ATT_V_ST) { vst = 0; vph ^= 1; }
        }
      }
    }
  } else {
    reg_alloc<232>();
    const int cw = __shfl_sync(0xffffffffu, wg - 1, 0);
    const int tid = threadIdx.x & 127;
    const int warp = tid >> 5, lane = tid & 31;
    const float sl2 = 0.08838834764831845f * 1.4426950408889634f;
    int kst = 0, vst = 0; uint32_t kph = 0, vph = 0;
    const uint64_t q_desc = make_desc(smem_u32(sm.q) + cw * 8192, 16, 1024);
    const uint64_t k_desc = make_desc(smem_u32(sm.k[0]), 16, 1024);
    const uint64_t v_desc = make_desc(smem_u32(sm.v[0]), 16384, 1024);
    float o[64], s[64];
    uint32_t p[32];
    uint32_t slot = 0;
    auto issue_qk = [&]() {
      mbar_wait(smem_u32(&sm.k_full[kst]), kph);
      const uint64_t kd = k_desc + (uint32_t)(kst * (ATT_TILE_BYTES >> 4));
      wgmma_fence();
#pragma unroll
      for (int ks = 0; ks < 8; ks++) {
        const uint32_t off = ((ks >> 2) * 16384 + (ks & 3) * 32) >> 4;
        wgmma_m64n128k16_ss<0>(s, q_desc + off, kd + off, ks > 0);
      }
      wgmma_commit();
    };
    auto issue_pv = [&]() {
      mbar_wait(smem_u32(&sm.v_full[vst]), vph);
      const uint64_t vd = v_desc + (uint32_t)(vst * (ATT_TILE_BYTES >> 4));
      wgmma_fence();
#pragma unroll
      for (int ks = 0; ks < 8; ks++) {
        wgmma_m64n128k16_rs<1>(o, p[4 * ks], p[4 * ks + 1], p[4 * ks + 2], p[4 * ks + 3], vd + (ks * 2048 >> 4), 1);
      }
      wgmma_commit();
    };
    auto release_k = [&]() {
      if (lane == 0) mbar_arrive(smem_u32(&sm.k_empty[kst]));
      if (++kst == ATT_K_ST) { kst = 0; kph ^= 1; }
    };
    auto release_v = [&]() {
      if (lane == 0) mbar_arrive(smem_u32(&sm.v_empty[vst]));
      if (++vst == ATT_V_ST) { vst = 0; vph ^= 1; }
    };
    auto sched_sync = [&]() {
      mbar_wait(smem_u32(&sm.ord[cw]), (slot & 1) ^ (cw ^ 1));
      slot++;
    };
    auto sched_arrive = [&]() {
      if (lane == 0) mbar_arrive(smem_u32(&sm.ord[cw ^ 1]));
    };

    for (int it = 0; it < ATT_ITEMS_PER_CTA; it++) {
      int head, qt; attn_item(cta, it, head, qt);
      float m0, m1, l0, l1, a0 = 1.f, a1 = 1.f;
#pragma unroll
      for (int i = 0; i < 64; i++) o[i] = 0.f;
      TI(0);
      mbar_wait(smem_u32(&sm.q_full), it & 1);
      TI(1);
      sched_sync();
      issue_qk();
      sched_arrive();
      wgmma_wait<0>();
      reg_fence(s);
      TI(2);
      release_k();
      if (qt == 0 && lane == 0) mbar_arrive(smem_u32(&sm.q_empty));
      {
        const int r0 = cw * 64 + warp * 16 + (lane >> 2);
#pragma unroll
        for (int j = 0; j < 16; j++) {
          int c = 8 * j + 2 * (lane & 3);
          if (c > r0) s[4 * j] = -INFINITY;
          if (c + 1 > r0) s[4 * j + 1] = -INFINITY;
          if (c > r0 + 8) s[4 * j + 2] = -INFINITY;
          if (c + 1 > r0 + 8) s[4 * j + 3] = -INFINITY;
        }
        float mx0 = fmaxf(s[0], s[1]), mx1 = fmaxf(s[2], s[3]);
#pragma unroll
        for (int j = 1; j < 16; j++) {
          mx0 = fmaxf(mx0, fmaxf(s[4 * j], s[4 * j + 1]));
          mx1 = fmaxf(mx1, fmaxf(s[4 * j + 2], s[4 * j + 3]));
        }
        mx0 = fmaxf(mx0, __shfl_xor_sync(0xffffffffu, mx0, 1));
        mx1 = fmaxf(mx1, __shfl_xor_sync(0xffffffffu, mx1, 1));
        mx0 = fmaxf(mx0, __shfl_xor_sync(0xffffffffu, mx0, 2));
        mx1 = fmaxf(mx1, __shfl_xor_sync(0xffffffffu, mx1, 2));
        m0 = mx0; m1 = mx1;
        const float ms0 = m0 * sl2, ms1 = m1 * sl2;
        l0 = 0.f; l1 = 0.f;
#pragma unroll
        for (int j = 0; j < 16; j++) {
          float p0 = ex2(fmaf(s[4 * j], sl2, -ms0));
          float p1 = ex2(fmaf(s[4 * j + 1], sl2, -ms0));
          float p2 = ex2(fmaf(s[4 * j + 2], sl2, -ms1));
          float p3 = ex2(fmaf(s[4 * j + 3], sl2, -ms1));
          l0 += p0 + p1; l1 += p2 + p3;
          p[2 * j] = pack_bf16(p0, p1);
          p[2 * j + 1] = pack_bf16(p2, p3);
        }
      }
      TI(3);
      for (int n = qt - 1; n >= 0; --n) {
        if (n != qt - 1) {
          TR(6);
          wgmma_wait<0>();
          reg_fence(o);
          TR(7);
          release_v();
#pragma unroll
          for (int j = 0; j < 16; j++) {
            p[2 * j] = pack_bf16(s[4 * j], s[4 * j + 1]);
            p[2 * j + 1] = pack_bf16(s[4 * j + 2], s[4 * j + 3]);
          }
        }
        TR(0);
        sched_sync();
        TR(1);
        issue_qk();
        TR(2);
#pragma unroll
        for (int j = 0; j < 16; j++) {
          o[4 * j] *= a0; o[4 * j + 1] *= a0; o[4 * j + 2] *= a1; o[4 * j + 3] *= a1;
        }
        issue_pv();
        TR(3);
        sched_arrive();
        wgmma_wait<1>();
        reg_fence(s);
        TR(4);
        release_k();
        if (n == 0 && lane == 0) mbar_arrive(smem_u32(&sm.q_empty));
        float mx0 = fmaxf(s[0], s[1]), mx1 = fmaxf(s[2], s[3]);
#pragma unroll
        for (int j = 1; j < 16; j++) {
          mx0 = fmaxf(mx0, fmaxf(s[4 * j], s[4 * j + 1]));
          mx1 = fmaxf(mx1, fmaxf(s[4 * j + 2], s[4 * j + 3]));
        }
        mx0 = fmaxf(mx0, __shfl_xor_sync(0xffffffffu, mx0, 1));
        mx1 = fmaxf(mx1, __shfl_xor_sync(0xffffffffu, mx1, 1));
        mx0 = fmaxf(mx0, __shfl_xor_sync(0xffffffffu, mx0, 2));
        mx1 = fmaxf(mx1, __shfl_xor_sync(0xffffffffu, mx1, 2));
        const float mn0 = fmaxf(m0, mx0), mn1 = fmaxf(m1, mx1);
        a0 = ex2((m0 - mn0) * sl2); a1 = ex2((m1 - mn1) * sl2);
        m0 = mn0; m1 = mn1;
        const float ms0 = mn0 * sl2, ms1 = mn1 * sl2;
        float rs0 = 0.f, rs1 = 0.f;
#pragma unroll
        for (int j = 0; j < 16; j++) {
          s[4 * j] = ex2(fmaf(s[4 * j], sl2, -ms0));
          s[4 * j + 1] = ex2(fmaf(s[4 * j + 1], sl2, -ms0));
          s[4 * j + 2] = ex2(fmaf(s[4 * j + 2], sl2, -ms1));
          s[4 * j + 3] = ex2(fmaf(s[4 * j + 3], sl2, -ms1));
          rs0 += s[4 * j] + s[4 * j + 1]; rs1 += s[4 * j + 2] + s[4 * j + 3];
        }
        l0 = l0 * a0 + rs0; l1 = l1 * a1 + rs1;
        reg_fence(s);
        TR(5);
      }
      if (qt > 0) {
        wgmma_wait<0>();
        reg_fence(o);
        release_v();
#pragma unroll
        for (int j = 0; j < 16; j++) {
          p[2 * j] = pack_bf16(s[4 * j], s[4 * j + 1]);
          p[2 * j + 1] = pack_bf16(s[4 * j + 2], s[4 * j + 3]);
        }
      }
      TI(4);
#pragma unroll
      for (int j = 0; j < 16; j++) {
        o[4 * j] *= a0; o[4 * j + 1] *= a0; o[4 * j + 2] *= a1; o[4 * j + 3] *= a1;
      }
      sched_sync();
      issue_pv();
      sched_arrive();
      l0 += __shfl_xor_sync(0xffffffffu, l0, 1); l0 += __shfl_xor_sync(0xffffffffu, l0, 2);
      l1 += __shfl_xor_sync(0xffffffffu, l1, 1); l1 += __shfl_xor_sync(0xffffffffu, l1, 2);
      const float inv0 = 1.f / l0, inv1 = 1.f / l1;
      wgmma_wait<0>();
      reg_fence(o);
      release_v();
      TI(5);
      if (tid == 0) tma_store_wait_read<0>();
      named_bar_sync(3 + cw, 128);
      {
        const int mi = lane >> 3;
        const int row = warp * 16 + (lane & 7) + (mi & 1) * 8;
        const uint32_t base = smem_u32(sm.ostage) + cw * 16384 + row * 128;
#pragma unroll
        for (int jj = 0; jj < 8; jj++) {
          uint32_t r0 = pack_bf16(o[8 * jj] * inv0, o[8 * jj + 1] * inv0);
          uint32_t r1 = pack_bf16(o[8 * jj + 2] * inv1, o[8 * jj + 3] * inv1);
          uint32_t r2 = pack_bf16(o[8 * jj + 4] * inv0, o[8 * jj + 5] * inv0);
          uint32_t r3 = pack_bf16(o[8 * jj + 6] * inv1, o[8 * jj + 7] * inv1);
          const int c = 2 * jj + (mi >> 1);
          const uint32_t addr = base + (c >> 3) * 8192 + (((c & 7) ^ (row & 7)) << 4);
          asm volatile("stmatrix.sync.aligned.m8n8.x4.shared.b16 [%0], {%1, %2, %3, %4};" ::"r"(addr), "r"(r0), "r"(r1), "r"(r2), "r"(r3) : "memory");
        }
      }
      fence_proxy_async_smem();
      named_bar_sync(3 + cw, 128);
      if (tid == 0) {
        tma_store_2d(&tmO, smem_u32(sm.ostage) + cw * 16384, head * HD, qt * 128 + cw * 64);
        tma_store_2d(&tmO, smem_u32(sm.ostage) + cw * 16384 + 8192, head * HD + 64, qt * 128 + cw * 64);
        tma_store_commit();
      }
      TI(6);
    }
    if (tid == 0) tma_store_wait<0>();
  }
}

__device__ __forceinline__ float bf16r(float x) { return __bfloat162float(__float2bfloat16_rn(x)); }

__global__ void __launch_bounds__(256) ln_kernel(const bf16* __restrict__ x, bf16* __restrict__ xn) {
  pdl_launch();
  const int row = blockIdx.x * 8 + (threadIdx.x >> 5);
  const int lane = threadIdx.x & 31;
  const uint4* src = reinterpret_cast<const uint4*>(x + (size_t)row * DM) + lane * 2;
  uint4 v0 = src[0], v1 = src[1];
  float f[16];
  const uint32_t w[8] = {v0.x, v0.y, v0.z, v0.w, v1.x, v1.y, v1.z, v1.w};
#pragma unroll
  for (int i = 0; i < 8; i++) { f[2 * i] = __uint_as_float(w[i] << 16); f[2 * i + 1] = __uint_as_float(w[i] & 0xffff0000u); }
  float s = 0.f;
#pragma unroll
  for (int i = 0; i < 16; i++) s += f[i];
#pragma unroll
  for (int o = 16; o > 0; o >>= 1) s += __shfl_xor_sync(0xffffffffu, s, o);
  const float mean = s * (1.f / DM);
  float ss = 0.f;
#pragma unroll
  for (int i = 0; i < 16; i++) { float d = f[i] - mean; ss += d * d; }
#pragma unroll
  for (int o = 16; o > 0; o >>= 1) ss += __shfl_xor_sync(0xffffffffu, ss, o);
  const float mb = bf16r(mean);
  const float vb = bf16r(ss * (1.f / DM));
  const float den = bf16r(sqrtf(bf16r(vb + 1e-5f)));
  uint32_t o8[8];
#pragma unroll
  for (int i = 0; i < 8; i++) {
    float a = bf16r(f[2 * i] - mb) / den, b = bf16r(f[2 * i + 1] - mb) / den;
    o8[i] = pack_bf16(a, b);
  }
  uint4* dst = reinterpret_cast<uint4*>(xn + (size_t)row * DM) + lane * 2;
  dst[0] = make_uint4(o8[0], o8[1], o8[2], o8[3]);
  dst[1] = make_uint4(o8[4], o8[5], o8[6], o8[7]);
}

#define PT(ev) do {} while (0)
constexpr int PJ_ST = 12;
constexpr int PJ_NT = 110;
constexpr int PJ_UNITS = 8 * PJ_NT;
struct ProjSmem {
  uint8_t ring[PJ_ST][16384];
  uint8_t ostage[2][16384];
  uint64_t full[PJ_ST], empty[PJ_ST];
  uint64_t ord[2];
};
constexpr int PJ_SMEM_BYTES = sizeof(ProjSmem) + 1024;
struct ProjParams {
  CUtensorMap a[2];
  CUtensorMap b[4];
  CUtensorMap o[4];
};

__device__ __forceinline__ void proj_decode(int u, int& p, int& asrc, int& bm, int& ncol) {
  p = u / PJ_NT;
  int t = u - p * PJ_NT;
  if (t < 64) { asrc = 0; bm = t >> 5; ncol = (t & 31) * 128; }
  else if (t < 96) { asrc = 1; bm = 2; ncol = (t - 64) * 128; }
  else { asrc = 1; bm = 3; ncol = (t - 96) * 128; }
}

__global__ void __cluster_dims__(2, 1, 1) __launch_bounds__(384, 1)
proj_kernel(const __grid_constant__ ProjParams prm) {
  extern __shared__ uint8_t smem_raw[];
  ProjSmem& sm = *reinterpret_cast<ProjSmem*>((reinterpret_cast<uintptr_t>(smem_raw) + 1023) & ~uintptr_t(1023));
  const int wg = threadIdx.x >> 7;
  const uint32_t rank = cluster_ctarank();
  const int cl = blockIdx.x >> 1;
  const int ncl = gridDim.x >> 1;
  const int u0 = (int)(((long long)cl * PJ_UNITS) / ncl), u1 = (int)(((long long)(cl + 1) * PJ_UNITS) / ncl);

  if (threadIdx.x == 0) {
    for (int s = 0; s < PJ_ST; s++) { mbar_init(smem_u32(&sm.full[s]), 1); mbar_init(smem_u32(&sm.empty[s]), 16); }
    mbar_init(smem_u32(&sm.ord[0]), 4); mbar_init(smem_u32(&sm.ord[1]), 4);
    fence_barrier_init();
  }
  __syncthreads();
  cluster_sync_all();
  pdl_launch();

  if (wg == 0) {
    reg_dealloc<40>();
    if (threadIdx.x == 0) {
      int st = 0; uint32_t ph = 0; int prev_key = -1; bool ln_waited = false;
      for (int u = u0; u < u1; u++) {
        int p, asrc, bm, ncol; proj_decode(u, p, asrc, bm, ncol);
        const int key = p * 2 + asrc;
        if (key != prev_key) {
          prev_key = key;
          if (asrc == 1 && !ln_waited) { pdl_wait(); ln_waited = true; }
          for (int c = 0; c < 8; c++) {
            mbar_wait(smem_u32(&sm.empty[st]), ph ^ 1);
            mbar_expect_tx(smem_u32(&sm.full[st]), 16384);
            tma_load_2d(smem_u32(sm.ring[st]), &prm.a[asrc], smem_u32(&sm.full[st]), c * 64, (2 * p + rank) * 128);
            if (++st == PJ_ST) { st = 0; ph ^= 1; }
          }
        }
        for (int c = 0; c < 8; c++) {
          mbar_wait(smem_u32(&sm.empty[st]), ph ^ 1);
          mbar_expect_tx(smem_u32(&sm.full[st]), 16384);
          tma_load_2d_mc(smem_u32(sm.ring[st]) + rank * 8192, &prm.b[bm], smem_u32(&sm.full[st]), ncol + rank * 64, c * 64, (uint16_t)3);
          if (++st == PJ_ST) { st = 0; ph ^= 1; }
        }
      }
    }
  } else {
    reg_alloc<232>();
    const int cw = __shfl_sync(0xffffffffu, wg - 1, 0);
    const int tid = threadIdx.x & 127;
    const int warp = tid >> 5, lane = tid & 31;
    const uint32_t peer = rank ^ 1;
    int st = 0; uint32_t ph = 0; int prev_key = -1;
    uint32_t a[32][4];
    float acc[64];
    const uint64_t b_desc = make_desc(smem_u32(sm.ring[0]), 8192, 1024);
    auto release = [&](int s) {
      if (lane == 0) mbar_arrive(smem_u32(&sm.empty[s]));
      else if (lane == 1) mbar_arrive_cluster(smem_u32(&sm.empty[s]), peer);
    };
    for (int u = u0; u < u1; u++) {
      int p, asrc, bm, ncol; proj_decode(u, p, asrc, bm, ncol);
      const int key = p * 2 + asrc;
      PT(0);
      if (key != prev_key) {
        prev_key = key;
        const int mi = lane >> 3;
        const int row = cw * 64 + warp * 16 + (lane & 7) + (mi & 1) * 8;
#pragma unroll
        for (int c = 0; c < 8; c++) {
          mbar_wait(smem_u32(&sm.full[st]), ph);
          const uint32_t base = smem_u32(sm.ring[st]) + row * 128;
#pragma unroll
          for (int ks = 0; ks < 4; ks++) {
            const int ch = 2 * ks + (mi >> 1);
            const uint32_t addr = base + ((ch ^ (row & 7)) << 4);
            asm volatile("ldmatrix.sync.aligned.m8n8.x4.shared.b16 {%0, %1, %2, %3}, [%4];"
                         : "=r"(a[4 * c + ks][0]), "=r"(a[4 * c + ks][1]), "=r"(a[4 * c + ks][2]), "=r"(a[4 * c + ks][3]) : "r"(addr) : "memory");
          }
          __syncwarp();
          release(st);
          if (++st == PJ_ST) { st = 0; ph ^= 1; }
        }
      }
      int prev_st = 0;
      PT(1);
      mbar_wait(smem_u32(&sm.ord[cw]), ((u - u0) & 1) ^ (cw ^ 1));
      PT(2);
#pragma unroll
      for (int c = 0; c < 8; c++) {
        mbar_wait(smem_u32(&sm.full[st]), ph);
        const uint64_t bd = b_desc + (uint32_t)(st * (16384 >> 4));
        wgmma_fence();
#pragma unroll
        for (int ks = 0; ks < 4; ks++)
          wgmma_m64n128k16_rs<1>(acc, a[4 * c + ks][0], a[4 * c + ks][1], a[4 * c + ks][2], a[4 * c + ks][3], bd + (ks * 2048 >> 4), (c | ks) != 0);
        wgmma_commit();
        if (c > 0) { wgmma_wait<1>(); release(prev_st); }
        prev_st = st;
        if (++st == PJ_ST) { st = 0; ph ^= 1; }
      }
      PT(3);
      if (lane == 0) mbar_arrive(smem_u32(&sm.ord[cw ^ 1]));
      wgmma_wait<0>();
      reg_fence(acc);
      release(prev_st);
      PT(4);
      if (tid == 0) tma_store_wait_read<0>();
      named_bar_sync(1 + cw, 128);
      {
        const int mi = lane >> 3;
        const int row = warp * 16 + (lane & 7) + (mi & 1) * 8;
        const uint32_t base = smem_u32(sm.ostage[cw]) + row * 128;
        const bool relu = (bm == 3);
#pragma unroll
        for (int jj = 0; jj < 8; jj++) {
          float v[8];
#pragma unroll
          for (int e = 0; e < 8; e++) v[e] = relu ? fmaxf(acc[8 * jj + e], 0.f) : acc[8 * jj + e];
          const int c = 2 * jj + (mi >> 1);
          const uint32_t addr = base + (c >> 3) * 8192 + (((c & 7) ^ (row & 7)) << 4);
          asm volatile("stmatrix.sync.aligned.m8n8.x4.shared.b16 [%0], {%1, %2, %3, %4};" ::"r"(addr), "r"(pack_bf16(v[0], v[1])),
                       "r"(pack_bf16(v[2], v[3])), "r"(pack_bf16(v[4], v[5])), "r"(pack_bf16(v[6], v[7])) : "memory");
        }
      }
      fence_proxy_async_smem();
      named_bar_sync(1 + cw, 128);
      if (tid == 0) {
        const int orow = (2 * p + rank) * 128 + cw * 64;
        tma_store_2d(&prm.o[bm], smem_u32(sm.ostage[cw]), ncol, orow);
        tma_store_2d(&prm.o[bm], smem_u32(sm.ostage[cw]) + 8192, ncol + 64, orow);
        tma_store_commit();
      }
      PT(5);
    }
    if (tid == 0) tma_store_wait<0>();
  }
  __syncthreads();
  cluster_sync_all();
}

constexpr int FN_ST = 4;
constexpr int FN_KB_Y = DFF / 64;
constexpr int FN_KB = FN_KB_Y + HDT / 64;
constexpr int FN_KPS = FN_KB / 4;
struct FinSmem {
  uint8_t a[FN_ST][16384];
  uint8_t b[FN_ST][32768];
  uint64_t full[FN_ST], empty[FN_ST];
};
constexpr int FN_SMEM_BYTES = sizeof(FinSmem) + 1024;
struct FinParams {
  CUtensorMap a[2];
  CUtensorMap b[2];
};
__device__ __align__(16) float4 g_part[5][32][32][256];
__device__ unsigned int g_fin_cnt[32], g_fin_done[32];

__device__ __forceinline__ void red_add_v2(float* p, float a, float b) {
  asm volatile("red.global.add.v2.f32 [%0], {%1, %2};" ::"l"(p), "f"(a), "f"(b) : "memory");
}

__global__ void __cluster_dims__(2, 1, 1) __launch_bounds__(384, 1)
fin_kernel(const __grid_constant__ FinParams prm, const bf16* __restrict__ x, bf16* __restrict__ out) {
  extern __shared__ uint8_t smem_raw[];
  FinSmem& sm = *reinterpret_cast<FinSmem*>((reinterpret_cast<uintptr_t>(smem_raw) + 1023) & ~uintptr_t(1023));
  const int wg = threadIdx.x >> 7;
  const uint32_t rank = cluster_ctarank();
  const int cl = blockIdx.x >> 1;
  const int ksl = cl & 3, tp = cl >> 2;
  const int mblk = (tp >> 1) * 2 + rank, nhalf = tp & 1;
  const int kb0 = ksl * FN_KPS;

  if (threadIdx.x == 0) {
    for (int s = 0; s < FN_ST; s++) { mbar_init(smem_u32(&sm.full[s]), 1); mbar_init(smem_u32(&sm.empty[s]), 16); }
    fence_barrier_init();
  }
  __syncthreads();
  cluster_sync_all();
  pdl_wait();

  if (wg == 0) {
    reg_dealloc<40>();
    if (threadIdx.x == 0) {
      int st = 0; uint32_t ph = 0;
      for (int i = 0; i < FN_KPS; i++) {
        const int kb = kb0 + i;
        const int src = kb < FN_KB_Y ? 0 : 1;
        const int kc = (src ? kb - FN_KB_Y : kb) * 64;
        mbar_wait(smem_u32(&sm.empty[st]), ph ^ 1);
        mbar_expect_tx(smem_u32(&sm.full[st]), 49152);
        tma_load_2d(smem_u32(sm.a[st]), &prm.a[src], smem_u32(&sm.full[st]), kc, mblk * 128);
#pragma unroll
        for (int j = 0; j < 2; j++) {
          const int box = rank * 2 + j;
          tma_load_2d_mc(smem_u32(sm.b[st]) + box * 8192, &prm.b[src], smem_u32(&sm.full[st]), nhalf * 256 + box * 64, kc, (uint16_t)3);
        }
        if (++st == FN_ST) { st = 0; ph ^= 1; }
      }
    }
  } else {
    reg_alloc<232>();
    const int cw = __shfl_sync(0xffffffffu, wg - 1, 0);
    const int tid = threadIdx.x & 127;
    const int warp = tid >> 5, lane = tid & 31;
    const uint32_t peer = rank ^ 1;
    int st = 0; uint32_t ph = 0;
    float acc[128];
    const uint64_t a_desc = make_desc(smem_u32(sm.a[0]) + cw * 8192, 16, 1024);
    const uint64_t b_desc = make_desc(smem_u32(sm.b[0]), 8192, 1024);
    const int row0 = mblk * 128 + cw * 64 + warp * 16 + (lane >> 2);
    const int col0 = nhalf * 256 + 2 * (lane & 3);
    const int tile = mblk * 2 + nhalf;
    auto flush = [&](int slot) {
      float4* dst = &g_part[slot][tile][0][threadIdx.x - 128];
#pragma unroll
      for (int j = 0; j < 32; j++) dst[j * 256] = make_float4(acc[4 * j], acc[4 * j + 1], acc[4 * j + 2], acc[4 * j + 3]);
    };
    int prev_st = -1;
    bool fresh = true;
    for (int i = 0; i < FN_KPS; i++) {
      const int kb = kb0 + i;
      if (kb == FN_KB_Y && i > 0) {
        wgmma_wait<0>();
        reg_fence(acc);
        if (lane == 0) mbar_arrive(smem_u32(&sm.empty[prev_st]));
        else if (lane == 1) mbar_arrive_cluster(smem_u32(&sm.empty[prev_st]), peer);
        prev_st = -1;
        flush(1);
        fresh = true;
      }
      mbar_wait(smem_u32(&sm.full[st]), ph);
      const uint64_t ad = a_desc + (uint32_t)(st * (16384 >> 4));
      const uint64_t bd = b_desc + (uint32_t)(st * (32768 >> 4));
      wgmma_fence();
#pragma unroll
      for (int ks = 0; ks < 4; ks++)
        wgmma_m64n256k16_ss<1>(acc, ad + (ks * 32 >> 4), bd + (ks * 2048 >> 4), !(fresh && ks == 0));
      wgmma_commit();
      fresh = false;
      if (prev_st >= 0) {
        wgmma_wait<1>();
        if (lane == 0) mbar_arrive(smem_u32(&sm.empty[prev_st]));
        else if (lane == 1) mbar_arrive_cluster(smem_u32(&sm.empty[prev_st]), peer);
      }
      prev_st = st;
      if (++st == FN_ST) { st = 0; ph ^= 1; }
    }
    wgmma_wait<0>();
    reg_fence(acc);
    if (lane == 0) mbar_arrive(smem_u32(&sm.empty[prev_st]));
    else if (lane == 1) mbar_arrive_cluster(smem_u32(&sm.empty[prev_st]), peer);
    flush(ksl == 0 ? 0 : ksl + 1);
    __threadfence();
    named_bar_sync(1, 256);
    if (threadIdx.x == 128) {
      atomicAdd(&g_fin_cnt[tile], 1u);
      unsigned int v;
      do { asm volatile("ld.acquire.gpu.global.u32 %0, [%1];" : "=r"(v) : "l"(&g_fin_cnt[tile]) : "memory"); } while (v < 4u);
    }
    named_bar_sync(1, 256);
    {
      const int t = threadIdx.x - 128;
      const int srct = 64 * ksl + (t & 63);
      const int jb = 8 * (t >> 6);
      float4 v[5][8];
#pragma unroll
      for (int sl = 0; sl < 5; sl++)
#pragma unroll
        for (int j = 0; j < 8; j++) v[sl][j] = __ldcg(&g_part[sl][tile][jb + j][srct]);
      const int l = srct & 31, wv = srct >> 5;
      const int r = mblk * 128 + (wv >> 2) * 64 + (wv & 3) * 16 + (l >> 2);
      uint32_t xr[8][2];
#pragma unroll
      for (int j = 0; j < 8; j++)
#pragma unroll
        for (int hh = 0; hh < 2; hh++)
          xr[j][hh] = *reinterpret_cast<const uint32_t*>(x + (size_t)(r + 8 * hh) * DM + nhalf * 256 + 8 * (jb + j) + 2 * (l & 3));
#pragma unroll
      for (int j = 0; j < 8; j++) {
        const int c = nhalf * 256 + 8 * (jb + j) + 2 * (l & 3);
        const float ys[4] = {v[0][j].x + v[1][j].x, v[0][j].y + v[1][j].y, v[0][j].z + v[1][j].z, v[0][j].w + v[1][j].w};
        const float ss[4] = {v[2][j].x + v[3][j].x + v[4][j].x, v[2][j].y + v[3][j].y + v[4][j].y,
                             v[2][j].z + v[3][j].z + v[4][j].z, v[2][j].w + v[3][j].w + v[4][j].w};
#pragma unroll
        for (int hh = 0; hh < 2; hh++) {
          const size_t off = (size_t)(r + 8 * hh) * DM + c;
          const uint32_t xv = xr[j][hh];
          float o[2];
#pragma unroll
          for (int e = 0; e < 2; e++) {
            const float y = bf16r(ys[2 * hh + e]);
            const float g = bf16r(__fdividef(y, 1.f + __expf(-y)));
            const float xe = e ? __uint_as_float(xv & 0xffff0000u) : __uint_as_float(xv << 16);
            o[e] = xe + bf16r(bf16r(ss[2 * hh + e]) * g);
          }
          *reinterpret_cast<uint32_t*>(out + off) = pack_bf16(o[0], o[1]);
        }
      }
    }
    named_bar_sync(1, 256);
    if (threadIdx.x == 128) {
      __threadfence();
      if (atomicAdd(&g_fin_done[tile], 1u) == 3u) { g_fin_cnt[tile] = 0u; g_fin_done[tile] = 0u; __threadfence(); }
    }
  }
  __syncthreads();
  cluster_sync_all();
}

typedef CUresult (*PFN_encodeTiled)(CUtensorMap*, CUtensorMapDataType, cuuint32_t, void*, const cuuint64_t*, const cuuint64_t*,
                                    const cuuint32_t*, const cuuint32_t*, CUtensorMapInterleave, CUtensorMapSwizzle,
                                    CUtensorMapL2promotion, CUtensorMapFloatOOBfill);

PFN_encodeTiled get_encode_fn() {
  static PFN_encodeTiled fn = nullptr;
  if (!fn) {
    void* p = nullptr;
    cudaDriverEntryPointQueryResult qr;
    cudaGetDriverEntryPoint("cuTensorMapEncodeTiled", &p, cudaEnableDefault, &qr);
    fn = (PFN_encodeTiled)p;
  }
  return fn;
}

CUtensorMap make_tmap(const void* ptr, uint64_t rows, uint64_t cols, uint32_t box_rows, uint32_t box_cols) {
  CUtensorMap tm;
  cuuint64_t gd[2] = {cols, rows};
  cuuint64_t gs[1] = {cols * 2};
  cuuint32_t box[2] = {box_cols, box_rows};
  cuuint32_t es[2] = {1, 1};
  get_encode_fn()(&tm, CU_TENSOR_MAP_DATA_TYPE_BFLOAT16, 2, const_cast<void*>(ptr), gd, gs, box, es, CU_TENSOR_MAP_INTERLEAVE_NONE,
                  CU_TENSOR_MAP_SWIZZLE_128B, CU_TENSOR_MAP_L2_PROMOTION_L2_256B, CU_TENSOR_MAP_FLOAT_OOB_FILL_NONE);
  return tm;
}

template <typename T> T* sym_addr(const T& sym) {
  void* p = nullptr;
  cudaGetSymbolAddress(&p, sym);
  return (T*)p;
}

}

template <typename... KArgs, typename... Args>
static void launch_pdl(void (*kern)(KArgs...), int grid, int block, int smem, Args... args) {
  cudaLaunchConfig_t cfg = {};
  cfg.gridDim = dim3(grid); cfg.blockDim = dim3(block); cfg.dynamicSmemBytes = smem; cfg.stream = cudaStreamPerThread;
  cudaLaunchAttribute at[1];
  at[0].id = cudaLaunchAttributeProgrammaticStreamSerialization;
  at[0].val.programmaticStreamSerializationAllowed = 1;
  cfg.attrs = at; cfg.numAttrs = 1;
  cudaLaunchKernelEx(&cfg, kern, KArgs(args)...);
}

extern "C" void kernel_launch(void* const* d_in, const int* in_sizes, int n_in, void* d_out, int out_size) {
  const bf16* x = (const bf16*)d_in[0];
  const bf16* ckv = (const bf16*)d_in[1];
  const bf16* wq = (const bf16*)d_in[2];
  const bf16* wuk = (const bf16*)d_in[3];
  const bf16* wuv = (const bf16*)d_in[4];
  const bf16* wo = (const bf16*)d_in[5];
  const bf16* w1 = (const bf16*)d_in[7];
  const bf16* w2 = (const bf16*)d_in[8];
  bf16* xn = sym_addr(g_xn[0]) ; bf16* q = sym_addr(g_q[0]); bf16* k = sym_addr(g_k[0]); bf16* v = sym_addr(g_v[0]);
  bf16* h = sym_addr(g_h[0]); bf16* ctx = sym_addr(g_ctx[0]);

  ln_kernel<<<SEQ / 8, 256>>>(x, xn);

  ProjParams pp;
  pp.a[0] = make_tmap(ckv, SEQ, DM, 128, 64);
  pp.a[1] = make_tmap(xn, SEQ, DM, 128, 64);
  pp.b[0] = make_tmap(wuk, DM, HDT, 64, 64);
  pp.b[1] = make_tmap(wuv, DM, HDT, 64, 64);
  pp.b[2] = make_tmap(wq, DM, HDT, 64, 64);
  pp.b[3] = make_tmap(w1, DM, DFF, 64, 64);
  pp.o[0] = make_tmap(k, SEQ, HDT, 64, 64);
  pp.o[1] = make_tmap(v, SEQ, HDT, 64, 64);
  pp.o[2] = make_tmap(q, SEQ, HDT, 64, 64);
  pp.o[3] = make_tmap(h, SEQ, DFF, 64, 64);
  cudaFuncSetAttribute(proj_kernel, cudaFuncAttributeMaxDynamicSharedMemorySize, PJ_SMEM_BYTES);
  launch_pdl(proj_kernel, 132, 384, PJ_SMEM_BYTES, pp);

  CUtensorMap tmQ = make_tmap(q, SEQ, HDT, 128, 64);
  CUtensorMap tmK = make_tmap(k, SEQ, HDT, 128, 64);
  CUtensorMap tmV = make_tmap(v, SEQ, HDT, 128, 64);
  CUtensorMap tmO = make_tmap(ctx, SEQ, HDT, 64, 64);
  cudaFuncSetAttribute(attn_kernel, cudaFuncAttributeMaxDynamicSharedMemorySize, ATT_SMEM_BYTES);
  launch_pdl(attn_kernel, 128, 384, ATT_SMEM_BYTES, tmQ, tmK, tmV, tmO);

  FinParams fp;
  fp.a[0] = make_tmap(h, SEQ, DFF, 128, 64);
  fp.a[1] = make_tmap(ctx, SEQ, HDT, 128, 64);
  fp.b[0] = make_tmap(w2, DFF, DM, 64, 64);
  fp.b[1] = make_tmap(wo, HDT, DM, 64, 64);
  cudaFuncSetAttribute(fin_kernel, cudaFuncAttributeMaxDynamicSharedMemorySize, FN_SMEM_BYTES);
  launch_pdl(fin_kernel, 128, 384, FN_SMEM_BYTES, fp, x, (bf16*)d_out);
}
```
